```python
import torch

def _softmax(x, axis=-1):
    return torch.softmax(x, dim=axis)
def _gelu(x):
    return torch.nn.functional.gelu(x, approximate="tanh")
def _silu(x):
    return torch.nn.functional.silu(x)
def _sigmoid(x):
    return torch.sigmoid(x)
def _layernorm(x, axis=-1, eps=1e-5):
    m = x.mean(dim=axis, keepdim=True)
    v = x.var(dim=axis, keepdim=True, unbiased=False)
    return (x - m) / torch.sqrt(v + eps)
def _scatter_add(tgt, idx, src, axis=0):
    return tgt.clone().index_add_(axis, idx, src)
def _segment_sum(src, seg, n):
    out = torch.zeros((n,) + src.shape[1:], dtype=src.dtype)
    return out.index_add_(0, seg, src)
def _pad(x, pw):
    flat = tuple(v for pair in reversed(pw) for v in pair)
    return torch.nn.functional.pad(x, flat)

kernel_name = 'parallel_sum__ssm_conv_h3__glu_gated_reglu__prompt'

def setup_inputs():

    _w = (lambda a: (lambda t: t.to(torch.bfloat16) if t.is_floating_point() else t)(torch.as_tensor(a)))
    def _A_setup():
        B, S, D = 1, 2048, 448
        ks = 4
        return {
            "q": _w((lambda *s: torch.randn(*s, dtype=torch.bfloat16) * 0.05)(B, S, D)),
            "k": _w((lambda *s: torch.randn(*s, dtype=torch.bfloat16) * 0.2)(B, S, D)),
            "v": _w((lambda *s: torch.randn(*s, dtype=torch.bfloat16) * 0.2)(B, S, D)),
            "shift_k": _w((lambda *s: torch.randn(*s, dtype=torch.bfloat16) * 0.2)(D, ks) * 0.5),
            "ssm_k": _w((lambda *s: torch.randn(*s, dtype=torch.bfloat16) * 0.4)(D, S) * (1.0 / S ** 0.5)),
            "ssm_D": _w((lambda *s: torch.randn(*s, dtype=torch.bfloat16) * 0.2)(D)),
        }
    _A_in = _A_setup()

    def _B_setup():
        B, S, D, F = 1, 2048, 448, 1792
        return {
            "x": _w((lambda *s: torch.randn(*s, dtype=torch.bfloat16) * 0.05)(B, S, D)),
            "W_gate": _w((lambda *s: torch.randn(*s, dtype=torch.bfloat16) * 0.2)(D, F) * (2.0 / D) ** 0.5),
            "W_up": _w((lambda *s: torch.randn(*s, dtype=torch.bfloat16) * 0.2)(D, F) * (2.0 / D) ** 0.5),
            "W_down": _w((lambda *s: torch.randn(*s, dtype=torch.bfloat16) * 0.2)(F, D) * (1.0 / F) ** 0.5),
        }
    _B_in = _B_setup()

    return {
        "A_q": _A_in["q"],
        "A_k": _A_in["k"],
        "A_v": _A_in["v"],
        "A_shift_k": _A_in["shift_k"],
        "A_ssm_k": _A_in["ssm_k"],
        "A_ssm_D": _A_in["ssm_D"],
        "B_x": _B_in["x"],
        "B_W_gate": _B_in["W_gate"],
        "B_W_up": _B_in["W_up"],
        "B_W_down": _B_in["W_down"],
    }

def reference(A_q, A_k, A_v, A_shift_k, A_ssm_k, A_ssm_D, B_x, B_W_gate, B_W_up, B_W_down):
    def _A_ref(q, k, v, shift_k, ssm_k, ssm_D):
        B, S, D = q.shape
        ks = shift_k.shape[-1]
        k_pad = _pad(k, ((0, 0), (ks - 1, 0), (0, 0)))
        k_shift = torch.zeros_like(k)
        for t in range(ks):
            k_shift = k_shift + k_pad[:, t:t + S, :] * shift_k[:, ks - 1 - t][None, None, :]
        kv = k_shift * v
        L = 2 * S
        kv_pad = _pad(kv, ((0, 0), (0, S), (0, 0)))
        kf_pad = _pad(ssm_k, ((0, 0), (0, S)))
        kv_f = (lambda x, axes=(-2,-1): torch.fft.rfft2(x.float(), dim=axes))(kv_pad[:, None, :, :], axes=(1, 2))
        kf_f = (lambda x, axes=(-2,-1): torch.fft.rfft2(x.float(), dim=axes))(kf_pad[:, None, :], axes=(1, 2))
        kf_f = (lambda x, *d: x.permute(*d))(kf_f, 1, 2, 0)
        y_f = kv_f * kf_f[None, :, :, :]
        y = (lambda x, s, axes=(-2,-1): torch.fft.irfft2(x, s=s, dim=axes).to(torch.bfloat16))(y_f, (1, L), axes=(1, 2))[:, 0, :S, :]
        y = y + kv * ssm_D[None, None, :]
        return q * y

    def _B_ref(x, W_gate, W_up, W_down):
        gate = torch.einsum("bsd,df->bsf", x, W_gate)
        up = torch.einsum("bsd,df->bsf", x, W_up)
        gate = gate * (lambda x, dt: x.to(dt))(gate > 0, gate.dtype)
        h = gate * up
        return torch.einsum("bsf,fd->bsd", h, W_down)

    x = A_q
    xn = _layernorm(x, axis=-1)
    return x + _A_ref(xn, A_k, A_v, A_shift_k, A_ssm_k, A_ssm_D) + _B_ref(xn, B_W_gate, B_W_up, B_W_down)
```

```cpp
#include <cuda_runtime.h>
#include <cuda.h>
#include <cuda_bf16.h>
#include <stdint.h>

namespace {

constexpr int S_ = 2048, D_ = 448, F_ = 1792;
constexpr int NCTA = 128;
constexpr int NTHREADS = 384;

constexpr int SM_XN = 0;
constexpr int SM_HS = 0;
constexpr int SM_RECV = 0;
constexpr int SM_WX = 32768;
constexpr int SM_RED = 0;
constexpr int RED_B = 4 * 12 * 512;
constexpr int SM_CH = 65536;
constexpr int CH_HB = 4128, CH_PAD = 112, CH_UH = 2048 + CH_PAD, CH_B = 8448;
constexpr int MAXCH = 5;
constexpr int SM_KVO = SM_CH;
constexpr int SM_KVK = SM_KVO + 14336;
constexpr int SM_KVV = SM_KVK + 160 * 112;
constexpr int SM_RING = 114688;
constexpr int NSLOT = 6, STAGE_B = 16384;
constexpr int SM_STATS = SM_RING + NSLOT * STAGE_B;
constexpr int SM_BARS = SM_STATS + 128;
constexpr int SM_DBG = SM_BARS + 512;
constexpr int SM_DBG2 = SM_DBG + 512;
constexpr int SM_TOTAL = SM_DBG2 + 1024;
constexpr int SMEM_BYTES = SM_TOTAL + 1024;
static_assert(SM_KVV + 128 * 112 <= SM_RING && SM_CH + MAXCH * CH_B <= SM_RING && SMEM_BYTES <= 232448, "smem map");
constexpr int SM_XT = SM_RING;
constexpr int SM_ZT = SM_RING + STAGE_B;
constexpr int SM_PT = SM_RING + 2 * STAGE_B;
constexpr int BAR_FULL = 0, BAR_EMPTY = 6, BAR_XF = 12, BAR_XFREE = 19, BAR_CFULL = 20, BAR_RECV = 25, BAR_PEER = 32, BAR_STG = 33,
              BAR_ZDONE = 34, BAR_XT = 39, BAR_ZT = 40, BAR_PT = 41, BAR_KVIN = 42, BAR_P0 = 43, BAR_STAT = 44, BAR_HFREE = 45, BAR_FULLX = 46, BAR_RFREE = 47, NBARS = 50;

__device__ uint4 g_part[16 * 8 * 4 * 28 * 32];
__device__ uint4 g_kvt[D_ * 256];
__device__ uint4 g_z[128 * D_ * 2];
__device__ unsigned int g_cnt_kv[8];
__device__ unsigned int g_cnt_z[8];
__device__ unsigned int g_cnt_part[128 * 8];
__device__ unsigned int g_epoch[NCTA * 8];
#define DBG_T(slot)
#define DBG_CK(slot)

__device__ __forceinline__ uint32_t gtime_lo() { uint32_t t; asm volatile("mov.u32 %0, %%globaltimer_lo;" : "=r"(t)); return t; }
__device__ __forceinline__ long long gtime() { unsigned long long t; asm volatile("mov.u64 %0, %%globaltimer;" : "=l"(t)); return (long long)t; }
__device__ __forceinline__ uint32_t smem_u32(const void* p) { return (uint32_t)__cvta_generic_to_shared(p); }
__device__ __forceinline__ void mbar_init(uint32_t bar, uint32_t cnt) { asm volatile("mbarrier.init.shared::cta.b64 [%0], %1;" ::"r"(bar), "r"(cnt) : "memory"); }
__device__ __forceinline__ void mbar_expect_tx(uint32_t bar, uint32_t bytes) { asm volatile("mbarrier.arrive.expect_tx.shared::cta.b64 _, [%0], %1;" ::"r"(bar), "r"(bytes) : "memory"); }
__device__ __forceinline__ void mbar_arrive(uint32_t bar) { asm volatile("mbarrier.arrive.shared::cta.b64 _, [%0];" ::"r"(bar) : "memory"); }
__device__ __forceinline__ bool mbar_try(uint32_t bar, uint32_t parity) {
  uint32_t ok;
  asm volatile("{\n.reg .pred p;\nmbarrier.try_wait.parity.shared::cta.b64 p, [%1], %2;\nselp.u32 %0, 1, 0, p;\n}" : "=r"(ok) : "r"(bar), "r"(parity) : "memory");
  return ok;
}
__device__ __forceinline__ void mbar_wait(uint32_t bar, uint32_t parity) {
  asm volatile("{\n.reg .pred p;\n.reg .u32 n;\nmov.u32 n, 0;\n"
               "WAIT_LOOP:\nmbarrier.try_wait.parity.shared::cta.b64 p, [%0], %1;\n@p bra WAIT_DONE;\n"
               "add.u32 n, n, 1;\nsetp.lt.u32 p, n, 262144;\n@p bra WAIT_LOOP;\nWAIT_DONE:\n}" ::"r"(bar), "r"(parity) : "memory");
}
__device__ __forceinline__ uint32_t ld_acquire(const unsigned int* p) { uint32_t v; asm volatile("ld.acquire.gpu.global.u32 %0, [%1];" : "=r"(v) : "l"(p) : "memory"); return v; }
__device__ __forceinline__ void wait_counter(const unsigned int* p, uint32_t target) {
  uint32_t n = 0;
#pragma unroll 1
  while ((int32_t)(ld_acquire(p) - target) < 0) { if (++n > (1u << 18)) break; }
}
__device__ __forceinline__ void signal_counter(unsigned int* p) {
  asm volatile("fence.acq_rel.gpu;\nred.relaxed.gpu.global.add.u32 [%0], 1;" ::"l"(p) : "memory");
}
__device__ __forceinline__ void fence_async_smem() { asm volatile("fence.proxy.async.shared::cta;" ::: "memory"); }
__device__ __forceinline__ void fence_async_all() { asm volatile("fence.proxy.async;" ::: "memory"); }
__device__ __forceinline__ void tma2d(uint32_t dst, const CUtensorMap* m, int c0, int c1, uint32_t bar) {
  asm volatile("cp.async.bulk.tensor.2d.shared::cluster.global.mbarrier::complete_tx::bytes [%0], [%1, {%3, %4}], [%2];"
               ::"r"(dst), "l"(m), "r"(bar), "r"(c0), "r"(c1) : "memory");
}
__device__ __forceinline__ void tma3d(uint32_t dst, const CUtensorMap* m, int c0, int c1, int c2, uint32_t bar) {
  asm volatile("cp.async.bulk.tensor.3d.shared::cluster.global.mbarrier::complete_tx::bytes [%0], [%1, {%3, %4, %5}], [%2];"
               ::"r"(dst), "l"(m), "r"(bar), "r"(c0), "r"(c1), "r"(c2) : "memory");
}
__device__ __forceinline__ void tma2d_prefetch(const CUtensorMap* m, int c0, int c1) {
  asm volatile("cp.async.bulk.prefetch.tensor.2d.L2.global.tile [%0, {%1, %2}];" ::"l"(m), "r"(c0), "r"(c1) : "memory");
}
__device__ __forceinline__ void tma5d_store(const CUtensorMap* m, uint32_t src, int c1, int c2, int c3, int c4) {
  asm volatile("cp.async.bulk.tensor.5d.global.shared::cta.bulk_group [%0, {%6, %2, %3, %4, %5}], [%1];"
               ::"l"(m), "r"(src), "r"(c1), "r"(c2), "r"(c3), "r"(c4), "r"(0) : "memory");
}
__device__ __forceinline__ void tma2d_store(const CUtensorMap* m, uint32_t src, int c0, int c1) {
  asm volatile("cp.async.bulk.tensor.2d.global.shared::cta.bulk_group [%0, {%2, %3}], [%1];" ::"l"(m), "r"(src), "r"(c0), "r"(c1) : "memory");
}
__device__ __forceinline__ void bulk_load(uint32_t dst, const void* src, uint32_t bytes, uint32_t bar) {
  asm volatile("cp.async.bulk.shared::cluster.global.mbarrier::complete_tx::bytes [%0], [%1], %2, [%3];" ::"r"(dst), "l"(src), "r"(bytes), "r"(bar) : "memory");
}
__device__ __forceinline__ void wg_fence() { asm volatile("wgmma.fence.sync.aligned;" ::: "memory"); }
__device__ __forceinline__ void wg_commit() { asm volatile("wgmma.commit_group.sync.aligned;" ::: "memory"); }
template <int n> __device__ __forceinline__ void wg_wait() { asm volatile("wgmma.wait_group.sync.aligned %0;" ::"n"(n) : "memory"); }
__device__ __forceinline__ uint64_t mkdesc(uint32_t addr, uint32_t lbo, uint32_t sbo, int sw) {
  return (uint64_t)((addr & 0x3FFFF) >> 4) | ((uint64_t)(lbo >> 4) << 16) | ((uint64_t)(sbo >> 4) << 32) | ((uint64_t)sw << 62);
}
__device__ __forceinline__ uint32_t lds32(uint32_t a) { uint32_t v; asm volatile("ld.shared.b32 %0, [%1];" : "=r"(v) : "r"(a)); return v; }
__device__ __forceinline__ uint4 lds128(uint32_t a) { uint4 v; asm volatile("ld.shared.v4.b32 {%0,%1,%2,%3}, [%4];" : "=r"(v.x), "=r"(v.y), "=r"(v.z), "=r"(v.w) : "r"(a)); return v; }
__device__ __forceinline__ void sts128(uint32_t a, uint32_t x, uint32_t y, uint32_t z, uint32_t w) { asm volatile("st.shared.v4.b32 [%0], {%1,%2,%3,%4};" ::"r"(a), "r"(x), "r"(y), "r"(z), "r"(w) : "memory"); }
__device__ __forceinline__ void sts128f(uint32_t a, float x, float y, float z, float w) { asm volatile("st.shared.v4.f32 [%0], {%1,%2,%3,%4};" ::"r"(a), "f"(x), "f"(y), "f"(z), "f"(w) : "memory"); }
__device__ __forceinline__ uint4 ldg128_nc(const void* p) { uint4 v; asm volatile("ld.global.nc.L1::no_allocate.v4.b32 {%0,%1,%2,%3}, [%4];" : "=r"(v.x), "=r"(v.y), "=r"(v.z), "=r"(v.w) : "l"(p)); return v; }
__device__ __forceinline__ uint4 ldg128_cg(const void* p) { uint4 v; asm volatile("ld.global.cg.v4.b32 {%0,%1,%2,%3}, [%4];" : "=r"(v.x), "=r"(v.y), "=r"(v.z), "=r"(v.w) : "l"(p) : "memory"); return v; }
__device__ __forceinline__ void named_bar(int id, int n) { asm volatile("bar.sync %0, %1;" ::"r"(id), "r"(n) : "memory"); }
__device__ __forceinline__ uint32_t pack_bf16(float lo, float hi) { uint32_t r; asm("cvt.rn.bf16x2.f32 %0, %1, %2;" : "=r"(r) : "f"(hi), "f"(lo)); return r; }
__device__ __forceinline__ uint32_t hmul2(uint32_t a, uint32_t b) { uint32_t r; asm("mul.rn.bf16x2 %0, %1, %2;" : "=r"(r) : "r"(a), "r"(b)); return r; }
__device__ __forceinline__ uint32_t hadd2(uint32_t a, uint32_t b) { uint32_t r; asm("add.rn.bf16x2 %0, %1, %2;" : "=r"(r) : "r"(a), "r"(b)); return r; }
__device__ __forceinline__ uint32_t hsub2(uint32_t a, uint32_t b) { uint32_t r; asm("sub.rn.bf16x2 %0, %1, %2;" : "=r"(r) : "r"(a), "r"(b)); return r; }
__device__ __forceinline__ uint32_t hfma2(uint32_t a, uint32_t b, uint32_t c) { uint32_t r; asm("fma.rn.bf16x2 %0, %1, %2, %3;" : "=r"(r) : "r"(a), "r"(b), "r"(c)); return r; }
__device__ __forceinline__ uint32_t hmax2(uint32_t a, uint32_t b) { uint32_t r; asm("max.bf16x2 %0, %1, %2;" : "=r"(r) : "r"(a), "r"(b)); return r; }
__device__ __forceinline__ float bf_lo(uint32_t w) { return __uint_as_float(w << 16); }
__device__ __forceinline__ float bf_hi(uint32_t w) { return __uint_as_float(w & 0xffff0000u); }
__device__ __forceinline__ float bf_round(float f) { return bf_lo(pack_bf16(f, 0.f)); }
template <int N> __device__ __forceinline__ void fence_acc(float (&d)[N]) {
#pragma unroll
  for (int i = 0; i < N; i++) asm volatile("" : "+f"(d[i])::"memory");
}
__device__ __forceinline__ void fence_r4(uint32_t& a, uint32_t& b, uint32_t& c, uint32_t& d) { asm volatile("" : "+r"(a), "+r"(b), "+r"(c), "+r"(d)::"memory"); }

__device__ __forceinline__ void bar_arrive(int id, int n) { asm volatile("bar.arrive %0, %1;" ::"r"(id), "r"(n) : "memory"); }
__device__ __forceinline__ uint32_t mapa(uint32_t addr, uint32_t rank) { uint32_t r; asm("mapa.shared::cluster.u32 %0, %1, %2;" : "=r"(r) : "r"(addr), "r"(rank)); return r; }
__device__ __forceinline__ void mbar_arrive_cluster(uint32_t remote_bar) { asm volatile("mbarrier.arrive.shared::cluster.b64 _, [%0];" ::"r"(remote_bar) : "memory"); }
__device__ __forceinline__ void st_async128(uint32_t remote_addr, uint32_t x, uint32_t y, uint32_t z, uint32_t w, uint32_t remote_bar) {
  asm volatile("st.async.weak.shared::cluster.mbarrier::complete_tx::bytes.v4.b32 [%0], {%1,%2,%3,%4}, [%5];"
               ::"r"(remote_addr), "r"(x), "r"(y), "r"(z), "r"(w), "r"(remote_bar) : "memory");
}
__device__ __forceinline__ void bulk_store(void* dst, uint32_t src, uint32_t bytes) {
  asm volatile("cp.async.bulk.global.shared::cta.bulk_group [%0], [%1], %2;" ::"l"(dst), "r"(src), "r"(bytes) : "memory");
}
__device__ __forceinline__ float sqrt_approx(float x) { float r; asm("sqrt.approx.ftz.f32 %0, %1;" : "=f"(r) : "f"(x)); return r; }
__device__ __forceinline__ float rcp_approx(float x) { float r; asm("rcp.approx.ftz.f32 %0, %1;" : "=f"(r) : "f"(x)); return r; }

__device__ __forceinline__ void mma16816(float (&d)[4], uint32_t a0, uint32_t a1, uint32_t a2, uint32_t a3, uint32_t b0, uint32_t b1) {
  asm volatile("mma.sync.aligned.m16n8k16.row.col.f32.bf16.bf16.f32 {%0,%1,%2,%3}, {%4,%5,%6,%7}, {%8,%9}, {%0,%1,%2,%3};"
               : "+f"(d[0]), "+f"(d[1]), "+f"(d[2]), "+f"(d[3]) : "r"(a0), "r"(a1), "r"(a2), "r"(a3), "r"(b0), "r"(b1));
}

template <int SC>
__device__ __forceinline__ void wgmma_rs_n128_mn(float (&d)[64], uint32_t a0, uint32_t a1, uint32_t a2, uint32_t a3, uint64_t db) {
  asm volatile("wgmma.mma_async.sync.aligned.m64n128k16.f32.bf16.bf16 "
    "{%0, %1, %2, %3, %4, %5, %6, %7, %8, %9, %10, %11, %12, %13, %14, %15, "
    "%16, %17, %18, %19, %20, %21, %22, %23, %24, %25, %26, %27, %28, %29, %30, %31, "
    "%32, %33, %34, %35, %36, %37, %38, %39, %40, %41, %42, %43, %44, %45, %46, %47, "
    "%48, %49, %50, %51, %52, %53, %54, %55, %56, %57, %58, %59, %60, %61, %62, %63}, "
    "{%64, %65, %66, %67}, %68, %69, 1, 1, 1;\n"
    : "+f"(d[0]), "+f"(d[1]), "+f"(d[2]), "+f"(d[3]), "+f"(d[4]), "+f"(d[5]), "+f"(d[6]), "+f"(d[7]),
      "+f"(d[8]), "+f"(d[9]), "+f"(d[10]), "+f"(d[11]), "+f"(d[12]), "+f"(d[13]), "+f"(d[14]), "+f"(d[15]),
      "+f"(d[16]), "+f"(d[17]), "+f"(d[18]), "+f"(d[19]), "+f"(d[20]), "+f"(d[21]), "+f"(d[22]), "+f"(d[23]),
      "+f"(d[24]), "+f"(d[25]), "+f"(d[26]), "+f"(d[27]), "+f"(d[28]), "+f"(d[29]), "+f"(d[30]), "+f"(d[31]),
      "+f"(d[32]), "+f"(d[33]), "+f"(d[34]), "+f"(d[35]), "+f"(d[36]), "+f"(d[37]), "+f"(d[38]), "+f"(d[39]),
      "+f"(d[40]), "+f"(d[41]), "+f"(d[42]), "+f"(d[43]), "+f"(d[44]), "+f"(d[45]), "+f"(d[46]), "+f"(d[47]),
      "+f"(d[48]), "+f"(d[49]), "+f"(d[50]), "+f"(d[51]), "+f"(d[52]), "+f"(d[53]), "+f"(d[54]), "+f"(d[55]),
      "+f"(d[56]), "+f"(d[57]), "+f"(d[58]), "+f"(d[59]), "+f"(d[60]), "+f"(d[61]), "+f"(d[62]), "+f"(d[63])
    : "r"(a0), "r"(a1), "r"(a2), "r"(a3), "l"(db), "n"(SC));
}
template <int SC>
__device__ __forceinline__ void wgmma_rs_n64_mn(float (&d)[32], uint32_t a0, uint32_t a1, uint32_t a2, uint32_t a3, uint64_t db) {
  asm volatile("wgmma.mma_async.sync.aligned.m64n64k16.f32.bf16.bf16 "
    "{%0, %1, %2, %3, %4, %5, %6, %7, %8, %9, %10, %11, %12, %13, %14, %15, "
    "%16, %17, %18, %19, %20, %21, %22, %23, %24, %25, %26, %27, %28, %29, %30, %31}, "
    "{%32, %33, %34, %35}, %36, %37, 1, 1, 1;\n"
    : "+f"(d[0]), "+f"(d[1]), "+f"(d[2]), "+f"(d[3]), "+f"(d[4]), "+f"(d[5]), "+f"(d[6]), "+f"(d[7]),
      "+f"(d[8]), "+f"(d[9]), "+f"(d[10]), "+f"(d[11]), "+f"(d[12]), "+f"(d[13]), "+f"(d[14]), "+f"(d[15]),
      "+f"(d[16]), "+f"(d[17]), "+f"(d[18]), "+f"(d[19]), "+f"(d[20]), "+f"(d[21]), "+f"(d[22]), "+f"(d[23]),
      "+f"(d[24]), "+f"(d[25]), "+f"(d[26]), "+f"(d[27]), "+f"(d[28]), "+f"(d[29]), "+f"(d[30]), "+f"(d[31])
    : "r"(a0), "r"(a1), "r"(a2), "r"(a3), "l"(db), "n"(SC));
}
template <int SC>
__device__ __forceinline__ void wgmma_rs_n32_k(float (&d)[16], uint32_t a0, uint32_t a1, uint32_t a2, uint32_t a3, uint64_t db) {
  asm volatile("wgmma.mma_async.sync.aligned.m64n32k16.f32.bf16.bf16 "
    "{%0, %1, %2, %3, %4, %5, %6, %7, %8, %9, %10, %11, %12, %13, %14, %15}, "
    "{%16, %17, %18, %19}, %20, %21, 1, 1, 0;\n"
    : "+f"(d[0]), "+f"(d[1]), "+f"(d[2]), "+f"(d[3]), "+f"(d[4]), "+f"(d[5]), "+f"(d[6]), "+f"(d[7]),
      "+f"(d[8]), "+f"(d[9]), "+f"(d[10]), "+f"(d[11]), "+f"(d[12]), "+f"(d[13]), "+f"(d[14]), "+f"(d[15])
    : "r"(a0), "r"(a1), "r"(a2), "r"(a3), "l"(db), "n"(SC));
}

__device__ __forceinline__ uint32_t ln_apply(uint32_t x2, uint32_t m2, uint32_t rh2, uint32_t rl2) {
  const uint32_t d = hsub2(x2, m2);
  return hfma2(d, rh2, hmul2(d, rl2));
}

struct Params {
  const __nv_bfloat16 *k, *v, *shift_k, *ssm_k, *ssm_D, *wg, *wu, *wd;
  int up_first;
};

constexpr int NCH_A = 2, NCH_B = 5;
#define PACE_NS 120
#define KVT0 6
constexpr int KV_T0 = KVT0;

struct Ring {
  uint32_t bars;
  uint32_t slot, phase;
  __device__ __forceinline__ void wait_full() const { mbar_wait(bars + 8 * (BAR_FULL + slot), phase); }
  __device__ __forceinline__ void release(bool elect) const { if (elect) mbar_arrive(bars + 8 * (BAR_EMPTY + slot)); }
  __device__ __forceinline__ void advance() { if (++slot == NSLOT) { slot = 0; phase ^= 1; } }
};
#define DBG_C(v)
#define DBG_ACC(a, x)

template <int NKB>
__device__ __forceinline__ void down_issue(float (&acc)[32], const uint32_t (&h)[64], uint64_t descB0, uint64_t descX, Ring& ring, int q, int g,
                                           bool pass_turn, uint32_t& s0, uint32_t& s1, bool elect) {
  uint64_t d0, d1;
  if (q == 3) {
    mbar_wait(ring.bars + 8 * BAR_FULLX, 0);
    d0 = descX; d1 = descX + STAGE_B / 16;
  } else {
    ring.wait_full();
    s0 = ring.slot;
    ring.advance();
    s1 = ring.slot;
    ring.advance();
    d0 = descB0 + s0 * (STAGE_B / 16); d1 = descB0 + s1 * (STAGE_B / 16);
  }
  named_bar(4 + g, 256);
  wg_fence();
#pragma unroll
  for (int ks = 0; ks < 8; ks++) {
    if (ks == 0) wgmma_rs_n64_mn<0>(acc, h[0], h[1], h[2], h[3], d0);
    else wgmma_rs_n64_mn<1>(acc, h[4 * ks], h[4 * ks + 1], h[4 * ks + 2], h[4 * ks + 3], d0 + ks * 128);
  }
  constexpr int HB = NKB == 8 ? 32 : 48;
#pragma unroll
  for (int ks = 0; ks < NKB; ks++) wgmma_rs_n64_mn<1>(acc, h[HB + 4 * ks], h[HB + 1 + 4 * ks], h[HB + 2 + 4 * ks], h[HB + 3 + 4 * ks], d1 + ks * 128);
  wg_commit();
  if (pass_turn) bar_arrive(4 + (g ^ 1), 256);
}
__device__ __forceinline__ void down_done(float (&acc)[32], uint32_t bars, int q, uint32_t s0, uint32_t s1, bool elect) {
  wg_wait<0>();
  fence_acc(acc);
  if (elect && q != 3) { mbar_arrive(bars + 8 * (BAR_EMPTY + s0)); mbar_arrive(bars + 8 * (BAR_EMPTY + s1)); }
}

template <int NKB>
__device__ __forceinline__ void phase2(const uint32_t (&h)[64], uint64_t descB0, uint64_t descX, Ring& ring, int g, bool keeper, bool elect,
                                       uint32_t sb, uint32_t peer_recv, uint32_t peer_bars, uint4* pout, int t128, int lane) {
  uint32_t sa = 0, sb2 = 0;
  if (!keeper) {
    float acc[32];
#pragma unroll 1
    for (int q = 0; q < 7; q++) {
      down_issue<NKB>(acc, h, descB0, descX, ring, q, g, true, sa, sb2, elect);
      if (q == 0) mbar_wait(ring.bars + 8 * BAR_PEER, 0);
      else if (q >= 4) mbar_wait(ring.bars + 8 * (BAR_RFREE + q - 4), 0);
      down_done(acc, ring.bars, q, sa, sb2, elect);
#pragma unroll
      for (int u = 0; u < 4; u++)
        st_async128(peer_recv + (q & 3) * 8192 + u * 512, pack_bf16(acc[8 * u], acc[8 * u + 1]), pack_bf16(acc[8 * u + 2], acc[8 * u + 3]),
                    pack_bf16(acc[8 * u + 4], acc[8 * u + 5]), pack_bf16(acc[8 * u + 6], acc[8 * u + 7]), peer_bars + 8 * (BAR_RECV + q));
    }
  } else {
    auto epi = [&](float (&acc)[32], int q) {
      mbar_wait(ring.bars + 8 * (BAR_RECV + q), 0);
      const uint32_t ra = sb + SM_RECV + (q & 3) * 8192 + (t128 >> 5) * 2048 + lane * 16;
      uint4 v[4];
#pragma unroll
      for (int u = 0; u < 4; u++) v[u] = lds128(ra + u * 512);
#pragma unroll
      for (int u = 0; u < 4; u++)
        pout[(4 * q + u) * 32] = make_uint4(hadd2(pack_bf16(acc[8 * u], acc[8 * u + 1]), v[u].x), hadd2(pack_bf16(acc[8 * u + 2], acc[8 * u + 3]), v[u].y),
                                            hadd2(pack_bf16(acc[8 * u + 4], acc[8 * u + 5]), v[u].z), hadd2(pack_bf16(acc[8 * u + 6], acc[8 * u + 7]), v[u].w));
      if (q < 3) { __syncwarp(); if (lane == 0) mbar_arrive_cluster(peer_bars + 8 * (BAR_RFREE + q)); }
    };
    float accA[32], accB[32];
    down_issue<NKB>(accA, h, descB0, descX, ring, 0, g, true, sa, sb2, elect);
    down_done(accA, ring.bars, 0, sa, sb2, elect);
#pragma unroll 1
    for (int m = 0; m < 3; m++) {
      down_issue<NKB>(accB, h, descB0, descX, ring, 2 * m + 1, g, true, sa, sb2, elect);
      epi(accA, 2 * m);
      down_done(accB, ring.bars, 2 * m + 1, sa, sb2, elect);
      down_issue<NKB>(accA, h, descB0, descX, ring, 2 * m + 2, g, m < 2, sa, sb2, elect);
      epi(accB, 2 * m + 1);
      down_done(accA, ring.bars, 2 * m + 2, sa, sb2, elect);
    }
    epi(accA, 6);
    __syncwarp();
    if (lane == 0) mbar_arrive(ring.bars + 8 * BAR_STG);
  }
}

__global__ void __cluster_dims__(2, 1, 1) __launch_bounds__(NTHREADS, 1)
fused_kernel(const __grid_constant__ CUtensorMap tm_wgu, const __grid_constant__ CUtensorMap tm_wd128, const __grid_constant__ CUtensorMap tm_wd64,
             const __grid_constant__ CUtensorMap tm_x128, const __grid_constant__ CUtensorMap tm_x16, const __grid_constant__ CUtensorMap tm_out,
             const __grid_constant__ CUtensorMap tm_k, const __grid_constant__ CUtensorMap tm_v, const __grid_constant__ CUtensorMap tm_kvt,
             const Params p) {
  extern __shared__ __align__(1024) uint8_t smem_raw[];
  const uint32_t sb = (smem_u32(smem_raw) + 1023u) & ~1023u;
  const int tid = threadIdx.x;
  const int warp = __shfl_sync(0xffffffffu, tid >> 5, 0);
  const int lane = tid & 31;
  const int bi = blockIdx.x >> 3, bj = blockIdx.x & 7;
  const int rank = bj & 1;
  const bool typeA = (bj & 2) == 0;
  const int natom = typeA ? 4 : 3;
  const int atom0 = 14 * (bj >> 2) + (typeA ? 4 * rank : 8 + 3 * rank);
  const int nch = typeA ? NCH_A : NCH_B;
  const int ch0 = (bi * 2 + (bj >> 2)) * (2 * NCH_A + 2 * NCH_B) + (typeA ? rank * NCH_A : 2 * NCH_A + rank * NCH_B);
  const int np1 = 7 * natom, nstage = np1 + 14, nring = np1 + 12;
  const uint32_t bars = sb + SM_BARS;
  auto BAR = [&](int i) { return bars + 8 * i; };
  auto load_gu = [&](int ps, int kc, uint32_t dst, uint32_t fb) {
    mbar_expect_tx(fb, 16384);
    tma3d(dst, &tm_wgu, (atom0 + ps) * 64, kc * 64, 0, fb);
  };
  auto load_wd = [&](int q, int hf, uint32_t dst, uint32_t fb) {
    if (hf == 0) mbar_expect_tx(fb, typeA ? 32768 : 24576);
    tma2d(dst, (typeA || hf == 0) ? &tm_wd128 : &tm_wd64, q * 64, (atom0 + 2 * hf) * 64, fb);
  };
  auto stage_prefetch = [&](int u) {
    if (u >= nstage) return;
#pragma unroll
    for (int i = 0; i < 4; i++) {
      const int r = lane + 32 * (i & 1), b = i >> 1;
      const __nv_bfloat16* a;
      if (u < np1) { const int ps = u / 7, kc = u - 7 * ps; a = (b ? p.wu : p.wg) + (size_t)(kc * 64 + r) * F_ + (atom0 + ps) * 64; }
      else {
        const int q = (u - np1) >> 1, hf = (u - np1) & 1;
        if (!typeA && hf == 1 && b == 1) continue;
        a = p.wd + (size_t)((atom0 + 2 * hf + b) * 64 + r) * D_ + q * 64;
      }
      asm volatile("prefetch.global.L2 [%0];" ::"l"(a));
    }
  };

  if (tid == 0) {
    DBG_T(0);
#pragma unroll
    for (int i = 0; i < 7; i++) mbar_init(BAR(BAR_XF + i), 1);
    mbar_init(BAR(BAR_FULL), 1); mbar_init(BAR(BAR_FULL + 1), 1);
    asm volatile("fence.mbarrier_init.release.cluster;" ::: "memory");
    fence_async_smem();
    DBG_CK(62);
#pragma unroll
    for (int kc = 0; kc < 7; kc++) {
      mbar_expect_tx(BAR(BAR_XF + kc), 16384);
      tma2d(sb + SM_XN + kc * 16384, &tm_x128, kc * 64, bi * 128, BAR(BAR_XF + kc));
    }
    DBG_CK(63);
    load_gu(0, 0, sb + SM_RING, BAR(BAR_FULL));
    DBG_CK(64);
    load_gu(0, 1, sb + SM_RING + STAGE_B, BAR(BAR_FULL + 1));
    DBG_CK(65);
  } else if (tid == 32) {
    asm volatile("prefetch.tensormap [%0];" ::"l"(&tm_wgu) : "memory");
#pragma unroll
    for (int i = 0; i < NBARS; i++) {
      if ((i >= BAR_XF && i < BAR_XF + 7) || i == BAR_FULL || i == BAR_FULL + 1) continue;
      uint32_t cnt = 1;
      if (i >= BAR_EMPTY && i < BAR_EMPTY + NSLOT) cnt = 2;
      else if (i == BAR_XFREE) cnt = 8;
      else if (i == BAR_P0) cnt = 2;
      else if (i == BAR_PEER || i == BAR_HFREE) cnt = 8;
      else if (i >= BAR_RFREE && i < BAR_RFREE + 3) cnt = 4;
      else if (i == BAR_STG || (i >= BAR_ZDONE && i < BAR_ZDONE + MAXCH)) cnt = 4;
      mbar_init(BAR(i), cnt);
    }
    asm volatile("fence.mbarrier_init.release.cluster;" ::: "memory");
#pragma unroll
    for (int q = 0; q < 7; q++) mbar_expect_tx(BAR(BAR_RECV + q), 8192);
  } else if (tid == 64) {
    asm volatile("prefetch.tensormap [%0];" ::"l"(&tm_wd128) : "memory");
    asm volatile("prefetch.tensormap [%0];" ::"l"(&tm_wd64) : "memory");
    asm volatile("prefetch.tensormap [%0];" ::"l"(&tm_k) : "memory");
    asm volatile("prefetch.tensormap [%0];" ::"l"(&tm_v) : "memory");
  }
  __syncthreads();
  if (tid == 0) DBG_CK(66);
  asm volatile("barrier.cluster.arrive.relaxed.aligned;" ::: "memory");

  if (warp < 4) {
    asm volatile("setmaxnreg.dec.sync.aligned.u32 72;");
    const uint32_t epoch = g_epoch[blockIdx.x * 8];
    if (warp == 0) {
      if (lane == 0) {
#pragma unroll 1
        for (int t = 2; t < NSLOT; t++) {
          mbar_wait(BAR(BAR_XF + (t == 5 ? 6 : 2 * t - 3)), 0);
          load_gu(0, t, sb + SM_RING + t * STAGE_B, BAR(BAR_FULL + t));
        }
        int slot = 0, ph = 0, ps = 0, kc = NSLOT;
#pragma unroll 1
        for (int t = NSLOT; t < np1; t++) {
          mbar_wait(BAR(BAR_EMPTY + slot), ph);
          load_gu(ps, kc, sb + SM_RING + slot * STAGE_B, BAR(BAR_FULL + slot));
          if (++kc == 7) { kc = 0; ps++; }
          if (t >= KV_T0 && t < KV_T0 + 9) {
            const int pc = (t - KV_T0) >> 1;
            if (t == KV_T0) mbar_expect_tx(BAR(BAR_KVIN), 160 * 112 + 128 * 112);
            if ((t - KV_T0) & 1) tma2d(sb + SM_KVV + pc * 32 * 112, &tm_v, 56 * bj, 128 * bi + 32 * pc, BAR(BAR_KVIN));
            else tma2d(sb + SM_KVK + pc * 32 * 112, &tm_k, 56 * bj, 128 * bi - 3 + 32 * pc, BAR(BAR_KVIN));
          }
          if (++slot == NSLOT) { slot = 0; ph ^= 1; }
        }
#pragma unroll 1
        for (int q = 0; q < 7; q++) {
          if (q == 3) continue;
          if (q == 2) {
            mbar_wait(BAR(BAR_HFREE), 0);
            load_wd(3, 0, sb + SM_WX, BAR(BAR_FULLX));
            load_wd(3, 1, sb + SM_WX + STAGE_B, BAR(BAR_FULLX));
          }
          const uint32_t fb = BAR(BAR_FULL + slot);
#pragma unroll
          for (int hf = 0; hf < 2; hf++) {
            mbar_wait(BAR(BAR_EMPTY + slot), ph);
            load_wd(q, hf, sb + SM_RING + slot * STAGE_B, fb);
            if (++slot == NSLOT) { slot = 0; ph ^= 1; }
          }
        }
      }
      if (lane == 0) {
        auto drain = [&](int s) { mbar_wait(BAR(BAR_EMPTY + s), ((nring - s + NSLOT - 1) / NSLOT - 1) & 1); };
        drain(0);
        mbar_expect_tx(BAR(BAR_XT), 14336);
        for (int q = 0; q < 7; q++) tma2d(sb + SM_XT + q * 2048, &tm_x16, q * 64, bi * 128 + bj * 16, BAR(BAR_XT));
        for (int s = 1; s < NSLOT; s++) drain(s);
        wait_counter(&g_cnt_part[blockIdx.x * 8], (epoch + 1) * 4);
        DBG_T(9);
        fence_async_all();
        mbar_expect_tx(BAR(BAR_PT), 4 * 14336);
        for (int s = 0; s < 4; s++) bulk_load(sb + SM_PT + s * 14336, g_part + ((size_t)blockIdx.x * 4 + s) * (28 * 32), 14336, BAR(BAR_PT));
        const int A = bi * 8 + bj;
        DBG_T(10);
        wait_counter(&g_cnt_z[0], (epoch + 1) * D_);
        DBG_T(11);
        fence_async_all();
        mbar_expect_tx(BAR(BAR_ZT), 14336);
        bulk_load(sb + SM_ZT, (const uint8_t*)g_z + (size_t)A * 14336, 14336, BAR(BAR_ZT));
      }
    } else {
      const int hw = warp - 1;
      const int pp = lane < 28 ? lane : 27;
      const int d = 56 * bj + 2 * pp;
      const uint2 sa = __ldg((const uint2*)(p.shift_k + d * 4)), sb2 = __ldg((const uint2*)(p.shift_k + d * 4 + 4));
      if (hw == 1) { mbar_wait(BAR(BAR_XF), 0); if (bi >= 2) stage_prefetch(bi); }
      mbar_wait(BAR(BAR_XF + 6), 0);
      {
        const int ht = tid - 32;
        for (int r = ht; r < 2 * 128; r += 96) {
          const size_t off = (size_t)(128 * bi + (r >> 1)) * D_ + 56 * bj + (r & 1) * 55;
          asm volatile("prefetch.global.L2 [%0];" ::"l"(p.k + off));
          asm volatile("prefetch.global.L2 [%0];" ::"l"(p.v + off));
        }
      }
      mbar_wait(BAR(BAR_P0), 0);
      if (hw == 1) stage_prefetch(bi + 16);
      for (int r = tid - 32; r < nch * 32; r += 96) asm volatile("prefetch.global.L2 [%0];" ::"l"(p.ssm_k + (size_t)ch0 * S_ + r * 64));
      const uint32_t sh0 = __byte_perm(sa.x, sb2.x, 0x5410), sh1 = __byte_perm(sa.x, sb2.x, 0x7632);
      const uint32_t sh2 = __byte_perm(sa.y, sb2.y, 0x5410), sh3 = __byte_perm(sa.y, sb2.y, 0x7632);
      mbar_wait(BAR(BAR_KVIN), 0);
      if (tid == 96) DBG_T(19);
#pragma unroll 1
      for (int c = hw; c < 8; c += 3) {
        const uint32_t ka = sb + SM_KVK + 16 * c * 112 + 4 * pp, va = sb + SM_KVV + 16 * c * 112 + 4 * pp;
        uint32_t w0[2][4], w1[2][4];
        uint32_t km3 = lds32(ka), km2 = lds32(ka + 112), km1 = lds32(ka + 224);
#pragma unroll
        for (int hh = 0; hh < 2; hh++) {
          uint32_t kv[8];
#pragma unroll
          for (int t = 0; t < 8; t++) {
            const uint32_t kk = lds32(ka + (8 * hh + t + 3) * 112), vv = lds32(va + (8 * hh + t) * 112);
            uint32_t a = hmul2(km3, sh3);
            a = hadd2(a, hmul2(km2, sh2));
            a = hadd2(a, hmul2(km1, sh1));
            a = hadd2(a, hmul2(kk, sh0));
            kv[t] = hmul2(a, vv);
            km3 = km2; km2 = km1; km1 = kk;
          }
#pragma unroll
          for (int q = 0; q < 2; q++) {
            w0[0][2 * hh + q] = __byte_perm(kv[4 * q + 3], kv[4 * q + 2], 0x5410);
            w1[0][2 * hh + q] = __byte_perm(kv[4 * q + 3], kv[4 * q + 2], 0x7632);
            w0[1][2 * hh + q] = __byte_perm(kv[4 * q + 1], kv[4 * q], 0x5410);
            w1[1][2 * hh + q] = __byte_perm(kv[4 * q + 1], kv[4 * q], 0x7632);
          }
        }
        if (lane < 28) {
#pragma unroll
          for (int half = 0; half < 2; half++) {
            const int r0 = half * 28 + pp, r1 = (2 + half) * 28 + pp;
            sts128(sb + SM_KVO + r0 * 128 + ((c ^ (r0 & 7)) << 4), w0[half][0], w0[half][1], w0[half][2], w0[half][3]);
            sts128(sb + SM_KVO + r1 * 128 + ((c ^ (r1 & 7)) << 4), w1[half][0], w1[half][1], w1[half][2], w1[half][3]);
          }
        }
      }
      fence_async_smem();
      named_bar(7, 96);
      if (tid == 96) DBG_T(20);
      if (hw == 1) { mbar_wait(BAR(BAR_P0), 1); stage_prefetch(bi + 32); }
      if (lane == 0) {
        if (hw == 2) {
#pragma unroll 1
          for (int i = 0; i < 4; i++) {
            tma5d_store(&tm_kvt, sb + SM_KVO + i * 28 * 128, 28 * bj, i & 1, i >> 1, bi);
            if (i < 3) __nanosleep(PACE_NS);
          }
          asm volatile("cp.async.bulk.commit_group;\ncp.async.bulk.wait_group 0;\nfence.proxy.async.global;" ::: "memory");
          DBG_T(21);
          signal_counter(&g_cnt_kv[0]);
          DBG_T(22);
        }
        if (hw == 0) {
          mbar_wait(BAR(BAR_STG), 0);
          asm volatile("fence.acq_rel.gpu;" ::: "memory");
#pragma unroll
          for (int w = 0; w < 4; w++) asm volatile("red.relaxed.gpu.global.add.u32 [%0], 1;" ::"l"(&g_cnt_part[(bi * 8 + 4 * rank + w) * 8]) : "memory");
        } else if (hw == 1) {
#pragma unroll 1
          for (int c2 = 0; c2 < nch; c2++) {
            mbar_wait(BAR(BAR_ZDONE + c2), 0);
            signal_counter(&g_cnt_z[0]);
          }
        }
      }
      __syncwarp();
      if (hw == 0) {
        mbar_wait(BAR(BAR_XT), 0);
        const int row = lane & 15, hf = lane >> 4;
        float s1 = 0.f, s2 = 0.f, s1b = 0.f, s2b = 0.f;
        uint32_t first = lds32(sb + SM_XT + row * 128 + ((row & 7) << 4));
        const float x0 = bf_lo(first);
#pragma unroll 1
        for (int q = 0; q < 7; q++) {
#pragma unroll
          for (int c = 0; c < 4; c++) {
            const uint4 v = lds128(sb + SM_XT + q * 2048 + row * 128 + (((4 * hf + c) ^ (row & 7)) << 4));
            const uint32_t ww[4] = {v.x, v.y, v.z, v.w};
#pragma unroll
            for (int i = 0; i < 4; i++) {
              const float lo = bf_lo(ww[i]) - x0, hi = bf_hi(ww[i]) - x0;
              s1 += lo; s2 = fmaf(lo, lo, s2); s1b += hi; s2b = fmaf(hi, hi, s2b);
            }
          }
        }
        s1 += s1b; s2 += s2b;
        s1 += __shfl_xor_sync(0xffffffffu, s1, 16); s2 += __shfl_xor_sync(0xffffffffu, s2, 16);
        const float dm = s1 * (1.f / D_);
        const float var = fmaxf(s2 * (1.f / D_) - dm * dm, 0.f);
        const float mb = bf_round(x0 + dm);
        const float rs = rcp_approx(bf_round(sqrt_approx(bf_round(bf_round(var) + 1e-5f))));
        if (hf == 0) asm volatile("st.shared.v2.b32 [%0], {%1, %2};" ::"r"(sb + SM_STATS + row * 8), "r"(pack_bf16(mb, mb)), "r"(__float_as_uint(rs)) : "memory");
        __syncwarp();
        if (lane == 0) mbar_arrive(BAR(BAR_STAT));
      }
      if (hw == 2) {
        for (int c = 0; c < nch; c++) {
          const uint32_t cb = sb + SM_CH + c * CH_B;
          if (lane < 2) sts128(cb + lane * 16, 0, 0, 0, 0);
          else if (lane < 16) { const int z = lane - 2; sts128(cb + CH_HB + (z / 7) * CH_UH + (z % 7) * 16, 0, 0, 0, 0); }
        }
        fence_async_smem();
        __syncwarp();
        if (lane == 0) {
          wait_counter(&g_cnt_kv[0], (epoch + 1) * NCTA);
          DBG_T(16);
          fence_async_all();
          for (int c = 0; c < nch; c++) {
            const uint32_t cb = sb + SM_CH + c * CH_B, cbar = BAR(BAR_CFULL + c);
            const int d = ch0 + c;
            mbar_expect_tx(cbar, 8192);
            bulk_load(cb + 32, p.ssm_k + (size_t)d * S_, 4096, cbar);
            bulk_load(cb + CH_HB + CH_PAD, (const uint8_t*)g_kvt + (size_t)d * 4096, 2048, cbar);
            bulk_load(cb + CH_HB + CH_PAD + CH_UH, (const uint8_t*)g_kvt + (size_t)d * 4096 + 2048, 2048, cbar);
            __nanosleep(PACE_NS);
          }
        }
        __syncwarp();
      }
    }
    named_bar(3, 128);
    if (tid == 0) g_epoch[blockIdx.x * 8] = epoch + 1;
  } else {
    asm volatile("setmaxnreg.inc.sync.aligned.u32 216;");
    const int cw = warp - 4, g = cw >> 2, w = cw & 3;
    const int t128 = tid & 127;
    const bool elect = t128 == 0;
    const bool keeper = g == rank;
    if (keeper) bar_arrive(4 + (g ^ 1), 256);
    if (tid == 128) DBG_CK(67);
    asm volatile("barrier.cluster.wait.aligned;" ::: "memory");
    if (tid == 128) DBG_CK(68);
    const uint64_t descB0 = mkdesc(sb + SM_RING, 8192, 1024, 1);
    Ring ring{bars, 0, 0};
    {
      uint32_t xf[28][4];
      float sum[4][4];
#pragma unroll
      for (int i = 0; i < 4; i++) sum[i][0] = sum[i][1] = sum[i][2] = sum[i][3] = 0.f;
      {
        const int xr = 64 * g + 16 * w + (lane & 7) + 8 * ((lane >> 3) & 1);
        const uint32_t xa = sb + SM_XN + xr * 128;
#pragma unroll
        for (int kc = 0; kc < 7; kc++) {
          mbar_wait(BAR(BAR_XF + kc), 0);
          if (elect && g == 0 && (kc == 0 || kc == 6)) DBG_T(kc == 0 ? 17 : 18);
#pragma unroll
          for (int ks = 0; ks < 4; ks++) {
            uint32_t(&f)[4] = xf[4 * kc + ks];
            asm volatile("ldmatrix.sync.aligned.m8n8.x4.shared.b16 {%0,%1,%2,%3}, [%4];" : "=r"(f[0]), "=r"(f[1]), "=r"(f[2]), "=r"(f[3])
                         : "r"(xa + kc * 16384 + (((2 * ks + (lane >> 4)) ^ (xr & 7)) << 4)));
            mma16816(sum[ks], f[0], f[1], f[2], f[3], 0x3F803F80u, 0x3F803F80u);
          }
        }
      }
      __syncwarp();
      if (lane == 0) mbar_arrive(BAR(BAR_XFREE));
      const float mean0 = ((sum[0][0] + sum[1][0]) + (sum[2][0] + sum[3][0])) * (1.f / D_), mean1 = ((sum[0][2] + sum[1][2]) + (sum[2][2] + sum[3][2])) * (1.f / D_);
      const float mb0 = bf_round(mean0), mb1 = bf_round(mean1);
      const uint32_t m20 = pack_bf16(mb0, mb0), m21 = pack_bf16(mb1, mb1);
      if (elect) DBG_T(1 + g);
      auto center = [&](int kc) {
#pragma unroll
        for (int ks = 0; ks < 4; ks++) {
          uint32_t(&f)[4] = xf[4 * kc + ks];
          f[0] = hsub2(f[0], m20); f[1] = hsub2(f[1], m21); f[2] = hsub2(f[2], m20); f[3] = hsub2(f[3], m21);
          fence_r4(f[0], f[1], f[2], f[3]);
        }
      };
      center(0);
      const uint32_t lo0 = p.up_first ? 0xFF80FF80u : 0u, lo1 = p.up_first ? 0u : 0xFF80FF80u;
      uint32_t h[64];
      const uint32_t ha0 = sb + SM_HS + g * 8192 + t128 * 16;
      auto gu_pass = [&](float (&acc)[64], int ps, auto hook) {
        uint32_t prev = 0;
#pragma unroll
        for (int kc = 0; kc < 7; kc++) {
          ring.wait_full();
          named_bar(4 + g, 256);
          wg_fence();
          const uint64_t db = descB0 + ring.slot * (STAGE_B / 16);
#pragma unroll
          for (int ks = 0; ks < 4; ks++) {
            const uint32_t(&f)[4] = xf[4 * kc + ks];
            if (kc == 0 && ks == 0) wgmma_rs_n128_mn<0>(acc, f[0], f[1], f[2], f[3], db);
            else wgmma_rs_n128_mn<1>(acc, f[0], f[1], f[2], f[3], db + ks * 128);
          }
          wg_commit();
          bar_arrive(4 + (g ^ 1), 256);
          if (kc > 0) { wg_wait<1>(); if (elect) mbar_arrive(BAR(BAR_EMPTY + prev)); }
          prev = ring.slot;
          ring.advance();
          hook(kc);
        }
        wg_wait<0>();
        fence_acc(acc);
        if (elect) mbar_arrive(BAR(BAR_EMPTY + prev));
      };
      auto h_word = [&](const float (&acc)[64], int o) {
        return hmul2(hmax2(pack_bf16(acc[o], acc[o + 1]), lo0), hmax2(pack_bf16(acc[32 + o], acc[33 + o]), lo1));
      };
#pragma unroll 1
      for (int ps = 0; ps < natom - 1; ps++) {
        float acc[64];
        gu_pass(acc, ps, [&](int kc) { if (ps == 0 && kc < 6) center(kc + 1); });
        if (ps == 0) mbar_wait(BAR(BAR_XFREE), 0);
#pragma unroll
        for (int u = 0; u < 4; u++)
          sts128(ha0 + ps * 16384 + u * 2048, h_word(acc, 8 * u), h_word(acc, 8 * u + 2), h_word(acc, 8 * u + 4), h_word(acc, 8 * u + 6));
        if (elect && ps < 2) mbar_arrive(BAR(BAR_P0));
        if (elect && ps == 0) DBG_T(3 + g);
      }
      {
        float acc[64];
        gu_pass(acc, natom - 1, [&](int kc) {
          if (kc >= 1 && kc <= 3) {
            if (kc < 3 || typeA) {
#pragma unroll
              for (int u = 0; u < 4; u++) {
                const uint4 v = lds128(ha0 + (kc - 1) * 16384 + u * 2048);
                const int o = 16 * (kc - 1) + 4 * u;
                h[o] = v.x; h[o + 1] = v.y; h[o + 2] = v.z; h[o + 3] = v.w;
              }
            } else {
#pragma unroll
              for (int i = 32; i < 48; i++) h[i] = 0;
            }
          }
          if (kc == 4) {
            __syncwarp();
            if (lane == 0) { mbar_arrive(BAR(BAR_HFREE)); mbar_arrive_cluster(mapa(BAR(BAR_PEER), rank ^ 1)); }
          }
        });
#pragma unroll
        for (int i = 0; i < 16; i++) h[48 + i] = h_word(acc, 2 * i);
        if (elect && natom == 2) mbar_arrive(BAR(BAR_P0));
      }
      if (elect) DBG_T(5 + g);
#pragma unroll
      for (int i = 0; i < 64; i += 4) fence_r4(h[i], h[i + 1], h[i + 2], h[i + 3]);
      const uint64_t descX = mkdesc(sb + SM_WX, 8192, 1024, 1);
      const uint32_t peer_recv = mapa(sb + SM_RECV + w * 2048 + lane * 16, rank ^ 1), peer_bars = mapa(bars, rank ^ 1);
      uint4* pout = g_part + ((size_t)(bi * 8 + cw) * 4 + (bj >> 1)) * (28 * 32) + lane;
      if (typeA) phase2<8>(h, descB0, descX, ring, g, keeper, elect, sb, peer_recv, peer_bars, pout, t128, lane);
      else phase2<4>(h, descB0, descX, ring, g, keeper, elect, sb, peer_recv, peer_bars, pout, t128, lane);
    }
    if (elect) DBG_T(7 + g);
    {
      const int r0 = lane >> 2, c = lane & 3;
      const uint32_t rbase = sb + SM_RED + g * RED_B;
#pragma unroll 1
      for (int ci = g; ci < nch; ci += 2) {
        const int d = ch0 + ci;
        const uint32_t cb = sb + SM_CH + ci * CH_B;
        const uint32_t D2 = __byte_perm((uint32_t)__ldg((const unsigned short*)p.ssm_D + d), 0, 0x1010);
        mbar_wait(BAR(BAR_CFULL + ci), 0);
        const uint32_t hw = cb + 32 + (128 * w + 2 * r0 - 4 * c - 2) * 2;
        const uint64_t db0 = mkdesc(cb + CH_HB + CH_PAD, CH_UH, 128, 0);
        float acc[4][16];
        uint32_t A[3][4][4];
        auto loadRaw = [&](int buf, int j) {
#pragma unroll
          for (int m = 0; m < 4; m++) {
            const uint32_t ad = hw + j * 32 + m * 1024;
            A[buf][m][1] = lds32(ad - 4); A[buf][m][0] = lds32(ad); A[buf][m][2] = lds32(ad + 4);
          }
        };
        loadRaw(0, 0); loadRaw(1, 1);
#pragma unroll
        for (int j = 0; j < 8; j++) {
          const int buf = j % 3;
#pragma unroll
          for (int m = 0; m < 4; m++) {
            A[buf][m][3] = __byte_perm(A[buf][m][0], A[buf][m][2], 0x5432);
            A[buf][m][1] = __byte_perm(A[buf][m][1], A[buf][m][0], 0x5432);
            fence_r4(A[buf][m][0], A[buf][m][1], A[buf][m][2], A[buf][m][3]);
          }
          wg_fence();
#pragma unroll
          for (int m = 0; m < 4; m++) {
#pragma unroll
            for (int gg = m; gg < 4; gg++) {
              if (j == 0 && m == 0) wgmma_rs_n32_k<0>(acc[gg], A[buf][m][0], A[buf][m][1], A[buf][m][2], A[buf][m][3], db0 + (32 * (gg - m) - j));
              else wgmma_rs_n32_k<1>(acc[gg], A[buf][m][0], A[buf][m][1], A[buf][m][2], A[buf][m][3], db0 + (uint64_t)(int64_t)(32 * (gg - m) - j));
            }
          }
          wg_commit();
          if (j < 6) {
            if (j > 0) wg_wait<1>();
            loadRaw((j + 2) % 3, j + 2);
          }
        }
        wg_wait<0>();
#pragma unroll
        for (int gg = 0; gg < 4; gg++) fence_acc(acc[gg]);
        if (ci == g) mbar_wait(BAR(BAR_STG), 0);
        named_bar(1 + g, 128);
        {
          const uint32_t rw = rbase + w * (12 * 512) + lane * 16;
#pragma unroll
          for (int gg = 0; gg < 4; gg++)
#pragma unroll
            for (int b = 1; b < 4; b++) sts128f(rw + (3 * gg + b - 1) * 512, acc[gg][4 * b], acc[gg][4 * b + 1], acc[gg][4 * b + 2], acc[gg][4 * b + 3]);
        }
        named_bar(1 + g, 128);
        float s[4][4];
#pragma unroll
        for (int i = 0; i < 4; i++) { s[i][0] = acc[i][0]; s[i][1] = acc[i][1]; s[i][2] = acc[i][2]; s[i][3] = acc[i][3]; }
#pragma unroll
        for (int dw = 1; dw < 4; dw++) {
          const int w2 = (w - dw) & 3;
          const bool wrap = w < dw;
          const uint32_t ra = rbase + w2 * (12 * 512) + (dw - 1 - (wrap ? 3 : 0)) * 512 + lane * 16;
#pragma unroll
          for (int i = 0; i < 4; i++) {
            if (i > 0 || !wrap) {
              const uint4 v = lds128(ra + i * 3 * 512);
              s[i][0] += __uint_as_float(v.x); s[i][1] += __uint_as_float(v.y); s[i][2] += __uint_as_float(v.z); s[i][3] += __uint_as_float(v.w);
            }
          }
        }
        const uint32_t ua = cb + CH_HB + CH_PAD + ((r0 & 1) ? 0 : CH_UH) + (8 * w + 2 * c) * 16 + (r0 >> 1) * 4;
        uint32_t* zp = (uint32_t*)g_z + ((size_t)(8 * w + 2 * c) * D_ + d) * 8 + (r0 ^ (d & 4));
#pragma unroll
        for (int i = 0; i < 4; i++) {
#pragma unroll
          for (int e = 0; e < 2; e++) {
            uint32_t kvw = lds32(ua + (32 * i + e) * 16);
            kvw = __byte_perm(kvw, kvw, 0x1032);
            zp[(size_t)(32 * i + e) * D_ * 8] = hadd2(pack_bf16(s[i][2 + e], s[i][e]), hmul2(kvw, D2));
          }
        }
        __syncwarp();
        if (lane == 0) mbar_arrive(BAR(BAR_ZDONE + ci));
      }
    }
    if (elect) DBG_T(12 + g);
    if (cw < 7) {
      const int r0 = lane >> 2;
      mbar_wait(BAR(BAR_XT), 0);
      mbar_wait(BAR(BAR_STAT), 0);
      uint32_t m2[2], rh2[2], rl2[2];
      float rsq[2];
#pragma unroll
      for (int e = 0; e < 2; e++) {
        uint32_t a, b;
        asm volatile("ld.shared.v2.b32 {%0, %1}, [%2];" : "=r"(a), "=r"(b) : "r"(sb + SM_STATS + (r0 + 8 * e) * 8));
        const float rs = __uint_as_float(b), rh = bf_round(rs);
        m2[e] = a; rh2[e] = pack_bf16(rh, rh); rl2[e] = pack_bf16(rs - rh, rs - rh); rsq[e] = rs * rs;
      }
      const int xr = (lane & 7) + 8 * ((lane >> 3) & 1);
      const uint32_t xbox = sb + SM_XT + cw * 2048 + xr * 128;
      uint32_t xf[4][4], bsum[4][4], xn[4][4];
#pragma unroll
      for (int u = 0; u < 4; u++) {
        const uint32_t xa = xbox + (((2 * u + (lane >> 4)) ^ (xr & 7)) << 4);
        asm volatile("ldmatrix.sync.aligned.m8n8.x4.shared.b16 {%0,%1,%2,%3}, [%4];" : "=r"(xf[u][0]), "=r"(xf[u][1]), "=r"(xf[u][2]), "=r"(xf[u][3]) : "r"(xa));
#pragma unroll
        for (int i = 0; i < 4; i++) xn[u][i] = ln_apply(xf[u][i], m2[i & 1], rh2[i & 1], rl2[i & 1]);
      }
      mbar_wait(BAR(BAR_PT), 0);
#pragma unroll
      for (int u = 0; u < 4; u++) {
        float a[8];
#pragma unroll
        for (int s = 0; s < 4; s++) {
          const uint4 v = lds128(sb + SM_PT + s * 14336 + ((4 * cw + u) * 32 + lane) * 16);
          if (s == 0) { a[0] = bf_lo(v.x); a[1] = bf_hi(v.x); a[2] = bf_lo(v.y); a[3] = bf_hi(v.y); a[4] = bf_lo(v.z); a[5] = bf_hi(v.z); a[6] = bf_lo(v.w); a[7] = bf_hi(v.w); }
          else { a[0] += bf_lo(v.x); a[1] += bf_hi(v.x); a[2] += bf_lo(v.y); a[3] += bf_hi(v.y); a[4] += bf_lo(v.z); a[5] += bf_hi(v.z); a[6] += bf_lo(v.w); a[7] += bf_hi(v.w); }
        }
        bsum[u][0] = pack_bf16(a[0] * rsq[0], a[1] * rsq[0]); bsum[u][1] = pack_bf16(a[2] * rsq[1], a[3] * rsq[1]);
        bsum[u][2] = pack_bf16(a[4] * rsq[0], a[5] * rsq[0]); bsum[u][3] = pack_bf16(a[6] * rsq[1], a[7] * rsq[1]);
      }
      mbar_wait(BAR(BAR_ZT), 0);
#pragma unroll
      for (int u = 0; u < 4; u++) {
        const int mi = lane >> 3;
        const int dz = 64 * cw + 16 * u + 8 * (mi >> 1) + (lane & 7);
        const uint32_t za = sb + SM_ZT + dz * 32 + (((mi & 1) ^ ((dz >> 2) & 1)) << 4);
        uint32_t z[4];
        asm volatile("ldmatrix.sync.aligned.m8n8.x4.trans.shared.b16 {%0,%1,%2,%3}, [%4];" : "=r"(z[0]), "=r"(z[1]), "=r"(z[2]), "=r"(z[3]) : "r"(za));
        uint32_t o[4];
#pragma unroll
        for (int i = 0; i < 4; i++) o[i] = hadd2(hadd2(xf[u][i], hmul2(xn[u][i], z[i])), bsum[u][i]);
        const uint32_t xa = xbox + (((2 * u + (lane >> 4)) ^ (xr & 7)) << 4);
        asm volatile("stmatrix.sync.aligned.m8n8.x4.shared.b16 [%0], {%1,%2,%3,%4};" ::"r"(xa), "r"(o[0]), "r"(o[1]), "r"(o[2]), "r"(o[3]) : "memory");
      }
      fence_async_smem();
      __syncwarp();
      if (lane == 0) {
        tma2d_store(&tm_out, sb + SM_XT + cw * 2048, cw * 64, bi * 128 + bj * 16);
        asm volatile("cp.async.bulk.commit_group;\ncp.async.bulk.wait_group.read 0;" ::: "memory");
      }
    }
    if (elect) DBG_T(14 + g);
  }
}

typedef CUresult (*EncodeFn)(CUtensorMap*, CUtensorMapDataType, cuuint32_t, void*, const cuuint64_t*, const cuuint64_t*, const cuuint32_t*,
                             const cuuint32_t*, CUtensorMapInterleave, CUtensorMapSwizzle, CUtensorMapL2promotion, CUtensorMapFloatOOBfill);

bool make_map(EncodeFn enc, CUtensorMap* m, const void* ptr, uint64_t inner, uint64_t outer, uint32_t box_inner, uint32_t box_outer,
              CUtensorMapSwizzle sw = CU_TENSOR_MAP_SWIZZLE_128B) {
  cuuint64_t dims[2] = {inner, outer};
  cuuint64_t strides[1] = {inner * 2};
  cuuint32_t box[2] = {box_inner, box_outer};
  cuuint32_t es[2] = {1, 1};
  return enc(m, CU_TENSOR_MAP_DATA_TYPE_BFLOAT16, 2, const_cast<void*>(ptr), dims, strides, box, es, CU_TENSOR_MAP_INTERLEAVE_NONE,
             sw, CU_TENSOR_MAP_L2_PROMOTION_L2_256B, CU_TENSOR_MAP_FLOAT_OOB_FILL_NONE) == CUDA_SUCCESS;
}

}

extern "C" void kernel_launch(void* const* d_in, const int* in_sizes, int n_in, void* d_out, int out_size) {
  (void)in_sizes; (void)n_in; (void)out_size;
  static EncodeFn enc = nullptr;
  if (!enc) {
    void* fn = nullptr;
    cudaDriverEntryPointQueryResult st;
    cudaGetDriverEntryPoint("cuTensorMapEncodeTiled", &fn, cudaEnableDefault, &st);
    enc = (EncodeFn)fn;
    cudaFuncSetAttribute(fused_kernel, cudaFuncAttributeMaxDynamicSharedMemorySize, SMEM_BYTES);
  }
  CUtensorMap tm_wgu, tm_wd128, tm_wd64, tm_x128, tm_x16, tm_out, tm_k, tm_v, tm_kvt;
  const uintptr_t pg = (uintptr_t)d_in[7], pu = (uintptr_t)d_in[8];
  {
    cuuint64_t dims[3] = {F_, D_, 2};
    cuuint64_t strides[2] = {F_ * 2, pg < pu ? pu - pg : pg - pu};
    cuuint32_t box[3] = {64, 64, 2};
    cuuint32_t es[3] = {1, 1, 1};
    enc(&tm_wgu, CU_TENSOR_MAP_DATA_TYPE_BFLOAT16, 3, (void*)(pg < pu ? pg : pu), dims, strides, box, es, CU_TENSOR_MAP_INTERLEAVE_NONE,
        CU_TENSOR_MAP_SWIZZLE_128B, CU_TENSOR_MAP_L2_PROMOTION_L2_256B, CU_TENSOR_MAP_FLOAT_OOB_FILL_NONE);
  }
  make_map(enc, &tm_x128, d_in[0], D_, S_, 64, 128);
  make_map(enc, &tm_wd128, d_in[9], D_, F_, 64, 128);
  make_map(enc, &tm_wd64, d_in[9], D_, F_, 64, 64);
  make_map(enc, &tm_x16, d_in[0], D_, S_, 64, 16);
  make_map(enc, &tm_out, d_out, D_, S_, 64, 16);
  Params p;
  make_map(enc, &tm_k, d_in[1], D_, S_, 56, 32, CU_TENSOR_MAP_SWIZZLE_NONE);
  make_map(enc, &tm_v, d_in[2], D_, S_, 56, 32, CU_TENSOR_MAP_SWIZZLE_NONE);
  {
    static void* kvt = nullptr;
    if (!kvt) cudaGetSymbolAddress(&kvt, g_kvt);
    cuuint64_t dims[5] = {64, 224, 2, 2, 16};
    cuuint64_t strides[4] = {8192, 2048, 4096, 128};
    cuuint32_t box[5] = {64, 28, 1, 1, 1};
    cuuint32_t es[5] = {1, 1, 1, 1, 1};
    enc(&tm_kvt, CU_TENSOR_MAP_DATA_TYPE_BFLOAT16, 5, kvt, dims, strides, box, es, CU_TENSOR_MAP_INTERLEAVE_NONE, CU_TENSOR_MAP_SWIZZLE_128B,
        CU_TENSOR_MAP_L2_PROMOTION_NONE, CU_TENSOR_MAP_FLOAT_OOB_FILL_NONE);
  }
  p.up_first = pu < pg;
  p.wg = (const __nv_bfloat16*)d_in[7];
  p.wu = (const __nv_bfloat16*)d_in[8];
  p.wd = (const __nv_bfloat16*)d_in[9];
  p.k = (const __nv_bfloat16*)d_in[1];
  p.v = (const __nv_bfloat16*)d_in[2];
  p.shift_k = (const __nv_bfloat16*)d_in[3];
  p.ssm_k = (const __nv_bfloat16*)d_in[4];
  p.ssm_D = (const __nv_bfloat16*)d_in[5];
  fused_kernel<<<NCTA, NTHREADS, SMEM_BYTES, cudaStreamPerThread>>>(tm_wgu, tm_wd128, tm_wd64, tm_x128, tm_x16, tm_out, tm_k, tm_v, tm_kvt, p);
}
```

```cpp
#include <cuda_runtime.h>
#include <cuda.h>
#include <cuda_bf16.h>
#include <stdint.h>

namespace {

constexpr int S_ = 2048, D_ = 448, F_ = 1792;
constexpr int NCTA = 128;
constexpr int NTHREADS = 384;

constexpr int SM_XN = 0;
constexpr int SM_HS = 0;
constexpr int SM_RECV = 0;
constexpr int SM_WX = 32768;
constexpr int SM_RED = 0;
constexpr int RED_B = 4 * 12 * 512;
constexpr int SM_CH = 65536;
#define SELF_POLL 0
#define REG_P 72
#define REG_C 216
#define P2_HOIST 0
#define P2_TURNS 1
#define CONV_MIX 1
#define CONV_VARN 0
#define RED_BF16 0
#define CONV_TURNS 1
#define CONV_N64 0
constexpr int CH_PAD = 7 * 16;
constexpr int CH_HB = 4128, CH_UH = 2048 + CH_PAD, CH_B = (CH_HB + 2 * CH_UH + 127) / 128 * 128;
constexpr int MAXCH = 5;
constexpr int SM_KVO = SM_CH;
constexpr int SM_KVK = SM_KVO + 14336;
constexpr int SM_KVV = SM_KVK + 160 * 112;
constexpr int SM_RING = 114688;
constexpr int STAGE_B = 16384;
constexpr int SM_SLOT6 = SM_HS + 49152;
constexpr int SM_STATS = SM_RING + 6 * STAGE_B;
constexpr int SM_BARS = SM_STATS + 128;
constexpr int SM_DBG = SM_BARS + 512;
constexpr int SM_DBG2 = SM_DBG + 512;
constexpr int SM_TOTAL = SM_DBG2 + 1024;
constexpr int SMEM_BYTES = SM_TOTAL + 1024;
static_assert(SM_KVV + 128 * 112 <= SM_RING && SM_CH + MAXCH * CH_B <= SM_RING && SMEM_BYTES <= 232448, "smem map");
constexpr int SM_XT = SM_RING;
constexpr int SM_ZT = SM_RING + STAGE_B;
constexpr int SM_PT = SM_RING + 2 * STAGE_B;
constexpr int BAR_FULL = 0, BAR_EMPTY = 7, BAR_XF = 14, BAR_XFREE = 21, BAR_CFULL = 22, BAR_RECV = 27, BAR_PEER = 34, BAR_STG = 35,
              BAR_ZDONE = 36, BAR_XT = 41, BAR_ZT = 42, BAR_PT = 43, BAR_KVIN = 44, BAR_P0 = 45, BAR_STAT = 46, BAR_HFREE = 47,
              BAR_RFREE = 48, BAR_FULL2 = 51, BAR_EMPTY2 = 55, NBARS = 59;
__host__ __device__ constexpr int gu_slot(int kc) { return kc < 6 ? SM_RING + kc * STAGE_B : SM_SLOT6; }
__host__ __device__ constexpr int wd_slot(int b) { return b < 3 ? SM_RING + b * 2 * STAGE_B : SM_WX; }

__device__ uint4 g_part[16 * 8 * 4 * 28 * 32];
__device__ uint4 g_kvt[D_ * 256];
__device__ uint4 g_z[2][128 * D_ * 2];
__device__ unsigned int g_cnt_kv[8];
__device__ unsigned int g_cnt_z[8];
__device__ unsigned int g_cnt_part[128 * 8];
__device__ unsigned int g_epoch[NCTA * 8];
#define DBG_T(slot)
#define DBG_CK(slot)

__device__ __forceinline__ uint32_t gtime_lo() { uint32_t t; asm volatile("mov.u32 %0, %%globaltimer_lo;" : "=r"(t)); return t; }
__device__ __forceinline__ long long gtime() { unsigned long long t; asm volatile("mov.u64 %0, %%globaltimer;" : "=l"(t)); return (long long)t; }
__device__ __forceinline__ uint32_t smem_u32(const void* p) { return (uint32_t)__cvta_generic_to_shared(p); }
__device__ __forceinline__ void mbar_init(uint32_t bar, uint32_t cnt) { asm volatile("mbarrier.init.shared::cta.b64 [%0], %1;" ::"r"(bar), "r"(cnt) : "memory"); }
__device__ __forceinline__ void mbar_expect_tx(uint32_t bar, uint32_t bytes) { asm volatile("mbarrier.arrive.expect_tx.shared::cta.b64 _, [%0], %1;" ::"r"(bar), "r"(bytes) : "memory"); }
__device__ __forceinline__ void mbar_arrive(uint32_t bar) { asm volatile("mbarrier.arrive.shared::cta.b64 _, [%0];" ::"r"(bar) : "memory"); }
__device__ __forceinline__ bool mbar_try(uint32_t bar, uint32_t parity) {
  uint32_t ok;
  asm volatile("{\n.reg .pred p;\nmbarrier.try_wait.parity.shared::cta.b64 p, [%1], %2;\nselp.u32 %0, 1, 0, p;\n}" : "=r"(ok) : "r"(bar), "r"(parity) : "memory");
  return ok;
}
__device__ __forceinline__ void mbar_wait(uint32_t bar, uint32_t parity) {
  asm volatile("{\n.reg .pred p;\n.reg .u32 n;\nmov.u32 n, 0;\n"
               "WAIT_LOOP:\nmbarrier.try_wait.parity.shared::cta.b64 p, [%0], %1;\n@p bra WAIT_DONE;\n"
               "add.u32 n, n, 1;\nsetp.lt.u32 p, n, 262144;\n@p bra WAIT_LOOP;\nWAIT_DONE:\n}" ::"r"(bar), "r"(parity) : "memory");
}
__device__ __forceinline__ uint32_t ld_acquire(const unsigned int* p) { uint32_t v; asm volatile("ld.acquire.gpu.global.u32 %0, [%1];" : "=r"(v) : "l"(p) : "memory"); return v; }
__device__ __forceinline__ void wait_counter(const unsigned int* p, uint32_t target) {
  uint32_t n = 0;
#pragma unroll 1
  while ((int32_t)(ld_acquire(p) - target) < 0) { if (++n > (1u << 18)) break; }
}
__device__ __forceinline__ void signal_counter(unsigned int* p) {
  asm volatile("fence.acq_rel.gpu;\nred.relaxed.gpu.global.add.u32 [%0], 1;" ::"l"(p) : "memory");
}
__device__ __forceinline__ void fence_async_smem() { asm volatile("fence.proxy.async.shared::cta;" ::: "memory"); }
__device__ __forceinline__ void fence_async_all() { asm volatile("fence.proxy.async;" ::: "memory"); }
__device__ __forceinline__ void tma2d(uint32_t dst, const CUtensorMap* m, int c0, int c1, uint32_t bar) {
  asm volatile("cp.async.bulk.tensor.2d.shared::cluster.global.mbarrier::complete_tx::bytes [%0], [%1, {%3, %4}], [%2];"
               ::"r"(dst), "l"(m), "r"(bar), "r"(c0), "r"(c1) : "memory");
}
__device__ __forceinline__ void tma3d(uint32_t dst, const CUtensorMap* m, int c0, int c1, int c2, uint32_t bar) {
  asm volatile("cp.async.bulk.tensor.3d.shared::cluster.global.mbarrier::complete_tx::bytes [%0], [%1, {%3, %4, %5}], [%2];"
               ::"r"(dst), "l"(m), "r"(bar), "r"(c0), "r"(c1), "r"(c2) : "memory");
}
__device__ __forceinline__ void tma2d_prefetch(const CUtensorMap* m, int c0, int c1) {
  asm volatile("cp.async.bulk.prefetch.tensor.2d.L2.global.tile [%0, {%1, %2}];" ::"l"(m), "r"(c0), "r"(c1) : "memory");
}
__device__ __forceinline__ void tma5d_store(const CUtensorMap* m, uint32_t src, int c1, int c2, int c3, int c4) {
  asm volatile("cp.async.bulk.tensor.5d.global.shared::cta.bulk_group [%0, {%6, %2, %3, %4, %5}], [%1];"
               ::"l"(m), "r"(src), "r"(c1), "r"(c2), "r"(c3), "r"(c4), "r"(0) : "memory");
}
__device__ __forceinline__ void tma2d_store(const CUtensorMap* m, uint32_t src, int c0, int c1) {
  asm volatile("cp.async.bulk.tensor.2d.global.shared::cta.bulk_group [%0, {%2, %3}], [%1];" ::"l"(m), "r"(src), "r"(c0), "r"(c1) : "memory");
}
__device__ __forceinline__ void bulk_load(uint32_t dst, const void* src, uint32_t bytes, uint32_t bar) {
  asm volatile("cp.async.bulk.shared::cluster.global.mbarrier::complete_tx::bytes [%0], [%1], %2, [%3];" ::"r"(dst), "l"(src), "r"(bytes), "r"(bar) : "memory");
}
__device__ __forceinline__ void wg_fence() { asm volatile("wgmma.fence.sync.aligned;" ::: "memory"); }
__device__ __forceinline__ void wg_commit() { asm volatile("wgmma.commit_group.sync.aligned;" ::: "memory"); }
template <int n> __device__ __forceinline__ void wg_wait() { asm volatile("wgmma.wait_group.sync.aligned %0;" ::"n"(n) : "memory"); }
__device__ __forceinline__ uint64_t mkdesc(uint32_t addr, uint32_t lbo, uint32_t sbo, int sw) {
  return (uint64_t)((addr & 0x3FFFF) >> 4) | ((uint64_t)(lbo >> 4) << 16) | ((uint64_t)(sbo >> 4) << 32) | ((uint64_t)sw << 62);
}
__device__ __forceinline__ uint32_t lds32(uint32_t a) { uint32_t v; asm volatile("ld.shared.b32 %0, [%1];" : "=r"(v) : "r"(a)); return v; }
__device__ __forceinline__ uint4 lds128(uint32_t a) { uint4 v; asm volatile("ld.shared.v4.b32 {%0,%1,%2,%3}, [%4];" : "=r"(v.x), "=r"(v.y), "=r"(v.z), "=r"(v.w) : "r"(a)); return v; }
__device__ __forceinline__ void sts128(uint32_t a, uint32_t x, uint32_t y, uint32_t z, uint32_t w) { asm volatile("st.shared.v4.b32 [%0], {%1,%2,%3,%4};" ::"r"(a), "r"(x), "r"(y), "r"(z), "r"(w) : "memory"); }
__device__ __forceinline__ void sts128f(uint32_t a, float x, float y, float z, float w) { asm volatile("st.shared.v4.f32 [%0], {%1,%2,%3,%4};" ::"r"(a), "f"(x), "f"(y), "f"(z), "f"(w) : "memory"); }
__device__ __forceinline__ uint4 ldg128_nc(const void* p) { uint4 v; asm volatile("ld.global.nc.L1::no_allocate.v4.b32 {%0,%1,%2,%3}, [%4];" : "=r"(v.x), "=r"(v.y), "=r"(v.z), "=r"(v.w) : "l"(p)); return v; }
__device__ __forceinline__ uint4 ldg128_cg(const void* p) { uint4 v; asm volatile("ld.global.cg.v4.b32 {%0,%1,%2,%3}, [%4];" : "=r"(v.x), "=r"(v.y), "=r"(v.z), "=r"(v.w) : "l"(p) : "memory"); return v; }
__device__ __forceinline__ void named_bar(int id, int n) { asm volatile("bar.sync %0, %1;" ::"r"(id), "r"(n) : "memory"); }
__device__ __forceinline__ uint32_t pack_bf16(float lo, float hi) { uint32_t r; asm("cvt.rn.bf16x2.f32 %0, %1, %2;" : "=r"(r) : "f"(hi), "f"(lo)); return r; }
__device__ __forceinline__ uint32_t hmul2(uint32_t a, uint32_t b) { uint32_t r; asm("mul.rn.bf16x2 %0, %1, %2;" : "=r"(r) : "r"(a), "r"(b)); return r; }
__device__ __forceinline__ uint32_t hadd2(uint32_t a, uint32_t b) { uint32_t r; asm("add.rn.bf16x2 %0, %1, %2;" : "=r"(r) : "r"(a), "r"(b)); return r; }
__device__ __forceinline__ uint32_t hsub2(uint32_t a, uint32_t b) { uint32_t r; asm("sub.rn.bf16x2 %0, %1, %2;" : "=r"(r) : "r"(a), "r"(b)); return r; }
__device__ __forceinline__ uint32_t hfma2(uint32_t a, uint32_t b, uint32_t c) { uint32_t r; asm("fma.rn.bf16x2 %0, %1, %2, %3;" : "=r"(r) : "r"(a), "r"(b), "r"(c)); return r; }
__device__ __forceinline__ uint32_t hmax2(uint32_t a, uint32_t b) { uint32_t r; asm("max.bf16x2 %0, %1, %2;" : "=r"(r) : "r"(a), "r"(b)); return r; }
__device__ __forceinline__ float bf_lo(uint32_t w) { return __uint_as_float(w << 16); }
__device__ __forceinline__ float bf_hi(uint32_t w) { return __uint_as_float(w & 0xffff0000u); }
__device__ __forceinline__ float bf_round(float f) { return bf_lo(pack_bf16(f, 0.f)); }
template <int N> __device__ __forceinline__ void fence_acc(float (&d)[N]) {
#pragma unroll
  for (int i = 0; i < N; i++) asm volatile("" : "+f"(d[i])::"memory");
}
__device__ __forceinline__ void fence_r4(uint32_t& a, uint32_t& b, uint32_t& c, uint32_t& d) { asm volatile("" : "+r"(a), "+r"(b), "+r"(c), "+r"(d)::"memory"); }

__device__ __forceinline__ void bar_arrive(int id, int n) { asm volatile("bar.arrive %0, %1;" ::"r"(id), "r"(n) : "memory"); }
__device__ __forceinline__ uint32_t mapa(uint32_t addr, uint32_t rank) { uint32_t r; asm("mapa.shared::cluster.u32 %0, %1, %2;" : "=r"(r) : "r"(addr), "r"(rank)); return r; }
__device__ __forceinline__ void mbar_arrive_cluster(uint32_t remote_bar) { asm volatile("mbarrier.arrive.shared::cluster.b64 _, [%0];" ::"r"(remote_bar) : "memory"); }
__device__ __forceinline__ void st_async128(uint32_t remote_addr, uint32_t x, uint32_t y, uint32_t z, uint32_t w, uint32_t remote_bar) {
  asm volatile("st.async.weak.shared::cluster.mbarrier::complete_tx::bytes.v4.b32 [%0], {%1,%2,%3,%4}, [%5];"
               ::"r"(remote_addr), "r"(x), "r"(y), "r"(z), "r"(w), "r"(remote_bar) : "memory");
}
__device__ __forceinline__ void bulk_store(void* dst, uint32_t src, uint32_t bytes) {
  asm volatile("cp.async.bulk.global.shared::cta.bulk_group [%0], [%1], %2;" ::"l"(dst), "r"(src), "r"(bytes) : "memory");
}
__device__ __forceinline__ float sqrt_approx(float x) { float r; asm("sqrt.approx.ftz.f32 %0, %1;" : "=f"(r) : "f"(x)); return r; }
__device__ __forceinline__ float rcp_approx(float x) { float r; asm("rcp.approx.ftz.f32 %0, %1;" : "=f"(r) : "f"(x)); return r; }

__device__ __forceinline__ void mma16816(float (&d)[4], uint32_t a0, uint32_t a1, uint32_t a2, uint32_t a3, uint32_t b0, uint32_t b1) {
  asm volatile("mma.sync.aligned.m16n8k16.row.col.f32.bf16.bf16.f32 {%0,%1,%2,%3}, {%4,%5,%6,%7}, {%8,%9}, {%0,%1,%2,%3};"
               : "+f"(d[0]), "+f"(d[1]), "+f"(d[2]), "+f"(d[3]) : "r"(a0), "r"(a1), "r"(a2), "r"(a3), "r"(b0), "r"(b1));
}

__device__ __forceinline__ int fresh_tid() { int t; asm volatile("mov.u32 %0, %%tid.x;" : "=r"(t)); return t; }
__device__ __forceinline__ int fresh_cta() { int t; asm volatile("mov.u32 %0, %%ctaid.x;" : "=r"(t)); return t; }

template <int SC>
__device__ __forceinline__ void wgmma_rs_n128_mn(float (&d)[64], uint32_t a0, uint32_t a1, uint32_t a2, uint32_t a3, uint64_t db) {
  asm volatile("wgmma.mma_async.sync.aligned.m64n128k16.f32.bf16.bf16 "
    "{%0, %1, %2, %3, %4, %5, %6, %7, %8, %9, %10, %11, %12, %13, %14, %15, "
    "%16, %17, %18, %19, %20, %21, %22, %23, %24, %25, %26, %27, %28, %29, %30, %31, "
    "%32, %33, %34, %35, %36, %37, %38, %39, %40, %41, %42, %43, %44, %45, %46, %47, "
    "%48, %49, %50, %51, %52, %53, %54, %55, %56, %57, %58, %59, %60, %61, %62, %63}, "
    "{%64, %65, %66, %67}, %68, %69, 1, 1, 1;\n"
    : "+f"(d[0]), "+f"(d[1]), "+f"(d[2]), "+f"(d[3]), "+f"(d[4]), "+f"(d[5]), "+f"(d[6]), "+f"(d[7]),
      "+f"(d[8]), "+f"(d[9]), "+f"(d[10]), "+f"(d[11]), "+f"(d[12]), "+f"(d[13]), "+f"(d[14]), "+f"(d[15]),
      "+f"(d[16]), "+f"(d[17]), "+f"(d[18]), "+f"(d[19]), "+f"(d[20]), "+f"(d[21]), "+f"(d[22]), "+f"(d[23]),
      "+f"(d[24]), "+f"(d[25]), "+f"(d[26]), "+f"(d[27]), "+f"(d[28]), "+f"(d[29]), "+f"(d[30]), "+f"(d[31]),
      "+f"(d[32]), "+f"(d[33]), "+f"(d[34]), "+f"(d[35]), "+f"(d[36]), "+f"(d[37]), "+f"(d[38]), "+f"(d[39]),
      "+f"(d[40]), "+f"(d[41]), "+f"(d[42]), "+f"(d[43]), "+f"(d[44]), "+f"(d[45]), "+f"(d[46]), "+f"(d[47]),
      "+f"(d[48]), "+f"(d[49]), "+f"(d[50]), "+f"(d[51]), "+f"(d[52]), "+f"(d[53]), "+f"(d[54]), "+f"(d[55]),
      "+f"(d[56]), "+f"(d[57]), "+f"(d[58]), "+f"(d[59]), "+f"(d[60]), "+f"(d[61]), "+f"(d[62]), "+f"(d[63])
    : "r"(a0), "r"(a1), "r"(a2), "r"(a3), "l"(db), "n"(SC));
}
template <int SC>
__device__ __forceinline__ void wgmma_rs_n64_mn(float (&d)[32], uint32_t a0, uint32_t a1, uint32_t a2, uint32_t a3, uint64_t db) {
  asm volatile("wgmma.mma_async.sync.aligned.m64n64k16.f32.bf16.bf16 "
    "{%0, %1, %2, %3, %4, %5, %6, %7, %8, %9, %10, %11, %12, %13, %14, %15, "
    "%16, %17, %18, %19, %20, %21, %22, %23, %24, %25, %26, %27, %28, %29, %30, %31}, "
    "{%32, %33, %34, %35}, %36, %37, 1, 1, 1;\n"
    : "+f"(d[0]), "+f"(d[1]), "+f"(d[2]), "+f"(d[3]), "+f"(d[4]), "+f"(d[5]), "+f"(d[6]), "+f"(d[7]),
      "+f"(d[8]), "+f"(d[9]), "+f"(d[10]), "+f"(d[11]), "+f"(d[12]), "+f"(d[13]), "+f"(d[14]), "+f"(d[15]),
      "+f"(d[16]), "+f"(d[17]), "+f"(d[18]), "+f"(d[19]), "+f"(d[20]), "+f"(d[21]), "+f"(d[22]), "+f"(d[23]),
      "+f"(d[24]), "+f"(d[25]), "+f"(d[26]), "+f"(d[27]), "+f"(d[28]), "+f"(d[29]), "+f"(d[30]), "+f"(d[31])
    : "r"(a0), "r"(a1), "r"(a2), "r"(a3), "l"(db), "n"(SC));
}
template <int SC>
__device__ __forceinline__ void wgmma_rs_n32_k(float (&d)[16], uint32_t a0, uint32_t a1, uint32_t a2, uint32_t a3, uint64_t db) {
  asm volatile("wgmma.mma_async.sync.aligned.m64n32k16.f32.bf16.bf16 "
    "{%0, %1, %2, %3, %4, %5, %6, %7, %8, %9, %10, %11, %12, %13, %14, %15}, "
    "{%16, %17, %18, %19}, %20, %21, 1, 1, 0;\n"
    : "+f"(d[0]), "+f"(d[1]), "+f"(d[2]), "+f"(d[3]), "+f"(d[4]), "+f"(d[5]), "+f"(d[6]), "+f"(d[7]),
      "+f"(d[8]), "+f"(d[9]), "+f"(d[10]), "+f"(d[11]), "+f"(d[12]), "+f"(d[13]), "+f"(d[14]), "+f"(d[15])
    : "r"(a0), "r"(a1), "r"(a2), "r"(a3), "l"(db), "n"(SC));
}
template <int SC>
__device__ __forceinline__ void wgmma_rs_n64_k(float (&d)[32], uint32_t a0, uint32_t a1, uint32_t a2, uint32_t a3, uint64_t db) {
  asm volatile("wgmma.mma_async.sync.aligned.m64n64k16.f32.bf16.bf16 "
    "{%0, %1, %2, %3, %4, %5, %6, %7, %8, %9, %10, %11, %12, %13, %14, %15, "
    "%16, %17, %18, %19, %20, %21, %22, %23, %24, %25, %26, %27, %28, %29, %30, %31}, "
    "{%32, %33, %34, %35}, %36, %37, 1, 1, 0;\n"
    : "+f"(d[0]), "+f"(d[1]), "+f"(d[2]), "+f"(d[3]), "+f"(d[4]), "+f"(d[5]), "+f"(d[6]), "+f"(d[7]),
      "+f"(d[8]), "+f"(d[9]), "+f"(d[10]), "+f"(d[11]), "+f"(d[12]), "+f"(d[13]), "+f"(d[14]), "+f"(d[15]),
      "+f"(d[16]), "+f"(d[17]), "+f"(d[18]), "+f"(d[19]), "+f"(d[20]), "+f"(d[21]), "+f"(d[22]), "+f"(d[23]),
      "+f"(d[24]), "+f"(d[25]), "+f"(d[26]), "+f"(d[27]), "+f"(d[28]), "+f"(d[29]), "+f"(d[30]), "+f"(d[31])
    : "r"(a0), "r"(a1), "r"(a2), "r"(a3), "l"(db), "n"(SC));
}
template <int SC>
__device__ __forceinline__ void wgmma_rs_n96_k(float (&d)[48], uint32_t a0, uint32_t a1, uint32_t a2, uint32_t a3, uint64_t db) {
  asm volatile("wgmma.mma_async.sync.aligned.m64n96k16.f32.bf16.bf16 "
    "{%0, %1, %2, %3, %4, %5, %6, %7, %8, %9, %10, %11, %12, %13, %14, %15, "
    "%16, %17, %18, %19, %20, %21, %22, %23, %24, %25, %26, %27, %28, %29, %30, %31, "
    "%32, %33, %34, %35, %36, %37, %38, %39, %40, %41, %42, %43, %44, %45, %46, %47}, "
    "{%48, %49, %50, %51}, %52, %53, 1, 1, 0;\n"
    : "+f"(d[0]), "+f"(d[1]), "+f"(d[2]), "+f"(d[3]), "+f"(d[4]), "+f"(d[5]), "+f"(d[6]), "+f"(d[7]),
      "+f"(d[8]), "+f"(d[9]), "+f"(d[10]), "+f"(d[11]), "+f"(d[12]), "+f"(d[13]), "+f"(d[14]), "+f"(d[15]),
      "+f"(d[16]), "+f"(d[17]), "+f"(d[18]), "+f"(d[19]), "+f"(d[20]), "+f"(d[21]), "+f"(d[22]), "+f"(d[23]),
      "+f"(d[24]), "+f"(d[25]), "+f"(d[26]), "+f"(d[27]), "+f"(d[28]), "+f"(d[29]), "+f"(d[30]), "+f"(d[31]),
      "+f"(d[32]), "+f"(d[33]), "+f"(d[34]), "+f"(d[35]), "+f"(d[36]), "+f"(d[37]), "+f"(d[38]), "+f"(d[39]),
      "+f"(d[40]), "+f"(d[41]), "+f"(d[42]), "+f"(d[43]), "+f"(d[44]), "+f"(d[45]), "+f"(d[46]), "+f"(d[47])
    : "r"(a0), "r"(a1), "r"(a2), "r"(a3), "l"(db), "n"(SC));
}
template <int SC>
__device__ __forceinline__ void wgmma_rs_n128_k(float (&d)[64], uint32_t a0, uint32_t a1, uint32_t a2, uint32_t a3, uint64_t db) {
  asm volatile("wgmma.mma_async.sync.aligned.m64n128k16.f32.bf16.bf16 "
    "{%0, %1, %2, %3, %4, %5, %6, %7, %8, %9, %10, %11, %12, %13, %14, %15, "
    "%16, %17, %18, %19, %20, %21, %22, %23, %24, %25, %26, %27, %28, %29, %30, %31, "
    "%32, %33, %34, %35, %36, %37, %38, %39, %40, %41, %42, %43, %44, %45, %46, %47, "
    "%48, %49, %50, %51, %52, %53, %54, %55, %56, %57, %58, %59, %60, %61, %62, %63}, "
    "{%64, %65, %66, %67}, %68, %69, 1, 1, 0;\n"
    : "+f"(d[0]), "+f"(d[1]), "+f"(d[2]), "+f"(d[3]), "+f"(d[4]), "+f"(d[5]), "+f"(d[6]), "+f"(d[7]),
      "+f"(d[8]), "+f"(d[9]), "+f"(d[10]), "+f"(d[11]), "+f"(d[12]), "+f"(d[13]), "+f"(d[14]), "+f"(d[15]),
      "+f"(d[16]), "+f"(d[17]), "+f"(d[18]), "+f"(d[19]), "+f"(d[20]), "+f"(d[21]), "+f"(d[22]), "+f"(d[23]),
      "+f"(d[24]), "+f"(d[25]), "+f"(d[26]), "+f"(d[27]), "+f"(d[28]), "+f"(d[29]), "+f"(d[30]), "+f"(d[31]),
      "+f"(d[32]), "+f"(d[33]), "+f"(d[34]), "+f"(d[35]), "+f"(d[36]), "+f"(d[37]), "+f"(d[38]), "+f"(d[39]),
      "+f"(d[40]), "+f"(d[41]), "+f"(d[42]), "+f"(d[43]), "+f"(d[44]), "+f"(d[45]), "+f"(d[46]), "+f"(d[47]),
      "+f"(d[48]), "+f"(d[49]), "+f"(d[50]), "+f"(d[51]), "+f"(d[52]), "+f"(d[53]), "+f"(d[54]), "+f"(d[55]),
      "+f"(d[56]), "+f"(d[57]), "+f"(d[58]), "+f"(d[59]), "+f"(d[60]), "+f"(d[61]), "+f"(d[62]), "+f"(d[63])
    : "r"(a0), "r"(a1), "r"(a2), "r"(a3), "l"(db), "n"(SC));
}

__device__ __forceinline__ uint32_t ln_apply(uint32_t x2, uint32_t m2, uint32_t rh2, uint32_t rl2) {
  const uint32_t d = hsub2(x2, m2);
  return hfma2(d, rh2, hmul2(d, rl2));
}

struct Params {
  const __nv_bfloat16 *x, *k, *v, *shift_k, *ssm_k, *ssm_D, *wg, *wu, *wd;
  __nv_bfloat16* out;
  int up_first;
};

constexpr int NCH_A = 2, NCH_B = 5;
#define NPF0 7
#define PACE_NS 120
#define KVT0 7
constexpr int KV_T0 = KVT0;

struct P2 {
  uint32_t sb, bars;
  int g;
  bool elect;
};
template <int NKB>
__device__ __forceinline__ void down_issue(float (&acc)[32], const uint32_t (&h)[64], P2& p2, int q, bool pass_turn, bool first_wg) {
  if (!P2_HOIST || q == 0) mbar_wait(p2.bars + 8 * (BAR_FULL2 + (q & 3)), q >> 2);
  const uint64_t d0 = mkdesc(p2.sb + ((q & 3) == 3 ? SM_WX : SM_RING + (q & 3) * 2 * STAGE_B), 8192, 1024, 1);
  if (P2_TURNS || q == 0) named_bar(4 + p2.g, 256);
  wg_fence();
#pragma unroll
  for (int ks = 0; ks < 8; ks++) {
    if (ks == 0) wgmma_rs_n64_mn<0>(acc, h[0], h[1], h[2], h[3], d0);
    else wgmma_rs_n64_mn<1>(acc, h[4 * ks], h[4 * ks + 1], h[4 * ks + 2], h[4 * ks + 3], d0 + ks * 128);
  }
  constexpr int HB = NKB == 8 ? 32 : 48;
#pragma unroll
  for (int ks = 0; ks < NKB; ks++) wgmma_rs_n64_mn<1>(acc, h[HB + 4 * ks], h[HB + 1 + 4 * ks], h[HB + 2 + 4 * ks], h[HB + 3 + 4 * ks], d0 + (8 + ks) * 128);
  wg_commit();
  if (pass_turn && (P2_TURNS || (q == 0 && pass_turn))) { if (P2_TURNS || first_wg) bar_arrive(4 + (p2.g ^ 1), 256); }
  if (P2_HOIST && q < 6) mbar_wait(p2.bars + 8 * (BAR_FULL2 + ((q + 1) & 3)), (q + 1) >> 2);
}
__device__ __forceinline__ void down_done(float (&acc)[32], P2& p2, int q) {
  wg_wait<0>();
  fence_acc(acc);
  if (p2.elect) mbar_arrive(p2.bars + 8 * (BAR_EMPTY2 + (q & 3)));
}

template <int NKB>
__device__ __forceinline__ void phase2(const uint32_t (&h)[64], P2& p2, bool keeper, uint32_t peer_recv, uint32_t peer_bars, uint4* pout,
                                       int t128, int lane) {
  if (!keeper) {
    float acc[32];
#pragma unroll 1
    for (int q = 0; q < 7; q++) {
      down_issue<NKB>(acc, h, p2, q, true, true);
      if (q == 0) mbar_wait(p2.bars + 8 * BAR_PEER, 0);
      else if (q >= 4) mbar_wait(p2.bars + 8 * (BAR_RFREE + q - 4), 0);
      down_done(acc, p2, q);
#pragma unroll
      for (int u = 0; u < 4; u++)
        st_async128(peer_recv + (q & 3) * 8192 + u * 512, pack_bf16(acc[8 * u], acc[8 * u + 1]), pack_bf16(acc[8 * u + 2], acc[8 * u + 3]),
                    pack_bf16(acc[8 * u + 4], acc[8 * u + 5]), pack_bf16(acc[8 * u + 6], acc[8 * u + 7]), peer_bars + 8 * (BAR_RECV + q));
    }
  } else {
    auto epi = [&](float (&acc)[32], int q) {
      mbar_wait(p2.bars + 8 * (BAR_RECV + q), 0);
      const uint32_t ra = p2.sb + SM_RECV + (q & 3) * 8192 + (t128 >> 5) * 2048 + lane * 16;
      uint4 v[4];
#pragma unroll
      for (int u = 0; u < 4; u++) v[u] = lds128(ra + u * 512);
#pragma unroll
      for (int u = 0; u < 4; u++)
        pout[(4 * q + u) * 32] = make_uint4(hadd2(pack_bf16(acc[8 * u], acc[8 * u + 1]), v[u].x), hadd2(pack_bf16(acc[8 * u + 2], acc[8 * u + 3]), v[u].y),
                                            hadd2(pack_bf16(acc[8 * u + 4], acc[8 * u + 5]), v[u].z), hadd2(pack_bf16(acc[8 * u + 6], acc[8 * u + 7]), v[u].w));
      if (q < 3) { __syncwarp(); if (lane == 0) mbar_arrive_cluster(peer_bars + 8 * (BAR_RFREE + q)); }
    };
    float accA[32], accB[32];
    down_issue<NKB>(accA, h, p2, 0, true, false);
    down_done(accA, p2, 0);
#pragma unroll 1
    for (int m = 0; m < 3; m++) {
      down_issue<NKB>(accB, h, p2, 2 * m + 1, true, false);
      epi(accA, 2 * m);
      down_done(accB, p2, 2 * m + 1);
      down_issue<NKB>(accA, h, p2, 2 * m + 2, m < 2, false);
      epi(accB, 2 * m + 1);
      down_done(accA, p2, 2 * m + 2);
    }
    epi(accA, 6);
    __syncwarp();
    if (lane == 0) mbar_arrive(p2.bars + 8 * BAR_STG);
  }
}

__global__ void __cluster_dims__(2, 1, 1) __launch_bounds__(NTHREADS, 1)
fused_kernel(const __grid_constant__ CUtensorMap tm_wgu, const __grid_constant__ CUtensorMap tm_wd128, const __grid_constant__ CUtensorMap tm_wd64,
             const __grid_constant__ CUtensorMap tm_x128, const __grid_constant__ CUtensorMap tm_x16,
             const __grid_constant__ CUtensorMap tm_k, const __grid_constant__ CUtensorMap tm_v, const __grid_constant__ CUtensorMap tm_kvt,
             const Params p) {
  extern __shared__ __align__(1024) uint8_t smem_raw[];
  const uint32_t sb = (smem_u32(smem_raw) + 1023u) & ~1023u;
  const int tid = threadIdx.x;
  const int warp = __shfl_sync(0xffffffffu, tid >> 5, 0);
  const int lane = tid & 31;
  const int bi = blockIdx.x >> 3, bj = blockIdx.x & 7;
  const int rank = bj & 1;
  const bool typeA = (bj & 2) == 0;
  const int natom = typeA ? 4 : 3;
  const int atom0 = 14 * (bj >> 2) + (typeA ? 4 * rank : 8 + 3 * rank);
  const int nch = typeA ? NCH_A : NCH_B;
  const int ch0 = (bi * 2 + (bj >> 2)) * (2 * NCH_A + 2 * NCH_B) + (typeA ? rank * NCH_A : 2 * NCH_A + rank * NCH_B);
  const int np1 = 7 * natom, nstage = np1 + 14;
  const uint32_t bars = sb + SM_BARS;
  auto BAR = [&](int i) { return bars + 8 * i; };
  auto load_gu = [&](int ps, int kc, uint32_t dst, uint32_t fb) {
    mbar_expect_tx(fb, 16384);
    tma3d(dst, &tm_wgu, (atom0 + ps) * 64, kc * 64, 0, fb);
  };
  auto load_wd = [&](int q) {
    const uint32_t dst = sb + ((q & 3) == 3 ? SM_WX : SM_RING + (q & 3) * 2 * STAGE_B), fb = BAR(BAR_FULL2 + (q & 3));
    mbar_expect_tx(fb, typeA ? 32768 : 24576);
    tma2d(dst, &tm_wd128, q * 64, atom0 * 64, fb);
    tma2d(dst + STAGE_B, typeA ? &tm_wd128 : &tm_wd64, q * 64, (atom0 + 2) * 64, fb);
  };
  auto stage_prefetch = [&](int u) {
    if (u >= nstage) return;
#pragma unroll
    for (int i = 0; i < 4; i++) {
      const int r = lane + 32 * (i & 1), b = i >> 1;
      const __nv_bfloat16* a;
      if (u < np1) { const int ps = u / 7, kc = u - 7 * ps; a = (b ? p.wu : p.wg) + (size_t)(kc * 64 + r) * F_ + (atom0 + ps) * 64; }
      else {
        const int q = (u - np1) >> 1, hf = (u - np1) & 1;
        if (!typeA && hf == 1 && b == 1) continue;
        a = p.wd + (size_t)((atom0 + 2 * hf + b) * 64 + r) * D_ + q * 64;
      }
      asm volatile("prefetch.global.L2 [%0];" ::"l"(a));
    }
  };

  if (tid >= 128) {
    const int t = tid - 128;
    if (t < 112) asm volatile("prefetch.global.L2 [%0];" ::"l"(p.x + (size_t)(128 * bi + 16 * bj) * D_ + t * 64));
    else if (t >= 128 && t < 128 + 8 * NPF0) {
      const int l = bi * 8 * NPF0 + (t - 128), st = l >> 7, b = (l >> 6) & 1, r = l & 63;
      asm volatile("prefetch.global.L2 [%0];" ::"l"((b ? p.wu : p.wg) + (size_t)(st * 64 + r) * F_ + atom0 * 64));
    }
  }
  if (tid == 0) {
    DBG_T(0);
#pragma unroll
    for (int i = 0; i < 7; i++) mbar_init(BAR(BAR_XF + i), 1);
    mbar_init(BAR(BAR_FULL), 1); mbar_init(BAR(BAR_FULL + 1), 1); mbar_init(BAR(BAR_FULL + 2), 1);
    asm volatile("fence.mbarrier_init.release.cluster;" ::: "memory");
    fence_async_smem();
    DBG_CK(62);
#pragma unroll
    for (int kc = 0; kc < 7; kc++) {
      mbar_expect_tx(BAR(BAR_XF + kc), 16384);
      tma2d(sb + SM_XN + kc * 16384, &tm_x128, kc * 64, bi * 128, BAR(BAR_XF + kc));
    }
    DBG_CK(63);
    load_gu(0, 0, sb + SM_RING, BAR(BAR_FULL));
    load_gu(0, 1, sb + SM_RING + STAGE_B, BAR(BAR_FULL + 1));
    load_gu(0, 2, sb + SM_RING + 2 * STAGE_B, BAR(BAR_FULL + 2));
    DBG_CK(65);
  } else if (tid == 32) {
    asm volatile("prefetch.tensormap [%0];" ::"l"(&tm_wgu) : "memory");
#pragma unroll
    for (int i = 0; i < NBARS; i++) {
      if ((i >= BAR_XF && i < BAR_XF + 7) || (i >= BAR_FULL && i < BAR_FULL + 3)) continue;
      uint32_t cnt = 1;
      if ((i >= BAR_EMPTY && i < BAR_EMPTY + 7) || (i >= BAR_EMPTY2 && i < BAR_EMPTY2 + 4)) cnt = 2;
      else if (i == BAR_XFREE) cnt = 8;
      else if (i == BAR_P0) cnt = 2;
      else if (i == BAR_PEER || i == BAR_HFREE) cnt = 8;
      else if (i >= BAR_RFREE && i < BAR_RFREE + 3) cnt = 4;
      else if (i == BAR_STG || (i >= BAR_ZDONE && i < BAR_ZDONE + MAXCH)) cnt = 4;
      mbar_init(BAR(i), cnt);
    }
    asm volatile("fence.mbarrier_init.release.cluster;" ::: "memory");
#pragma unroll
    for (int q = 0; q < 7; q++) mbar_expect_tx(BAR(BAR_RECV + q), 8192);
  } else if (tid == 64) {
    asm volatile("prefetch.tensormap [%0];" ::"l"(&tm_wd128) : "memory");
    asm volatile("prefetch.tensormap [%0];" ::"l"(&tm_wd64) : "memory");
    asm volatile("prefetch.tensormap [%0];" ::"l"(&tm_k) : "memory");
    asm volatile("prefetch.tensormap [%0];" ::"l"(&tm_v) : "memory");
  }
  __syncthreads();
  if (tid == 0) DBG_CK(66);
  asm volatile("barrier.cluster.arrive.relaxed.aligned;" ::: "memory");

  if (warp < 4) {
    asm volatile("setmaxnreg.dec.sync.aligned.u32 %0;" ::"n"(REG_P));
    const uint32_t epoch = g_epoch[blockIdx.x * 8];
    if (warp == 0) {
      if (lane == 0) {
#pragma unroll 1
        for (int kc = 3; kc < 7; kc++) {
          mbar_wait(BAR(kc == 6 ? BAR_XFREE : BAR_XF + 2 * kc - 6), 0);
          load_gu(0, kc, sb + (kc < 6 ? SM_RING + kc * STAGE_B : SM_SLOT6), BAR(BAR_FULL + kc));
        }
        asm volatile("st.shared.b32 [%0], %1;" ::"r"(sb + SM_BARS + 480), "r"(epoch) : "memory");
        int t = 7;
#pragma unroll 1
        for (int ps = 1; ps < natom; ps++) {
#pragma unroll 1
          for (int kc = 0; kc < 7; kc++, t++) {
            mbar_wait(BAR(BAR_EMPTY + kc), (ps - 1) & 1);
            load_gu(ps, kc, sb + (kc < 6 ? SM_RING + kc * STAGE_B : SM_SLOT6), BAR(BAR_FULL + kc));
            if (t >= KV_T0 && t < KV_T0 + 5) {
              const int pc = t - KV_T0;
              if (pc == 0) mbar_expect_tx(BAR(BAR_KVIN), 160 * 112 + 128 * 112);
              tma2d(sb + SM_KVK + pc * 32 * 112, &tm_k, 56 * bj, 128 * bi - 3 + 32 * pc, BAR(BAR_KVIN));
              if (pc < 4) tma2d(sb + SM_KVV + pc * 32 * 112, &tm_v, 56 * bj, 128 * bi + 32 * pc, BAR(BAR_KVIN));
            }
          }
        }
        const int lastph = (natom - 1) & 1;
#pragma unroll 1
        for (int q = 0; q < 7; q++) {
          if (q < 3) { mbar_wait(BAR(BAR_EMPTY + 2 * q), lastph); mbar_wait(BAR(BAR_EMPTY + 2 * q + 1), lastph); }
          else if (q == 3) { mbar_wait(BAR(BAR_HFREE), 0); mbar_wait(BAR(BAR_EMPTY + 6), lastph); }
          else mbar_wait(BAR(BAR_EMPTY2 + (q & 3)), 0);
          load_wd(q);
        }
        mbar_wait(BAR(BAR_EMPTY2 + 0), 1);
        mbar_expect_tx(BAR(BAR_XT), 14336);
        for (int q = 0; q < 7; q++) tma2d(sb + SM_XT + q * 2048, &tm_x16, q * 64, bi * 128 + bj * 16, BAR(BAR_XT));
        mbar_wait(BAR(BAR_EMPTY2 + 1), 1);
        mbar_wait(BAR(BAR_EMPTY2 + 2), 1);
        wait_counter(&g_cnt_part[blockIdx.x * 8], (epoch + 1) * 4);
        DBG_T(9);
        fence_async_all();
        mbar_expect_tx(BAR(BAR_PT), 4 * 14336);
        for (int s = 0; s < 4; s++) bulk_load(sb + SM_PT + s * 14336, g_part + ((size_t)blockIdx.x * 4 + s) * (28 * 32), 14336, BAR(BAR_PT));
        DBG_T(10);
        {
          const uint32_t target = (epoch + 1) * D_;
          uint32_t n = 0, v;
#pragma unroll 1
          do { asm volatile("ld.relaxed.gpu.global.u32 %0, [%1];" : "=r"(v) : "l"(&g_cnt_z[0]) : "memory"); } while ((int32_t)(v - target) < 0 && ++n < (1u << 18));
        }
        DBG_T(11);
        mbar_arrive(BAR(BAR_ZT));
      }
    } else {
      const int hw = warp - 1;
      const int pp = lane < 28 ? lane : 27;
      const int d = 56 * bj + 2 * pp;
      const uint2 sa = __ldg((const uint2*)(p.shift_k + d * 4)), sb2 = __ldg((const uint2*)(p.shift_k + d * 4 + 4));
      if (hw == 1) { mbar_wait(BAR(BAR_XF), 0); if (bi >= NPF0) stage_prefetch(bi); }
      mbar_wait(BAR(BAR_XF + 6), 0);
      {
        const int ht = tid - 32;
        for (int r = ht; r < 2 * 128; r += 96) {
          const size_t off = (size_t)(128 * bi + (r >> 1)) * D_ + 56 * bj + (r & 1) * 55;
          asm volatile("prefetch.global.L2 [%0];" ::"l"(p.k + off));
          asm volatile("prefetch.global.L2 [%0];" ::"l"(p.v + off));
        }
      }
      mbar_wait(BAR(BAR_P0), 0);
      if (hw == 1) stage_prefetch(bi + 16);
      for (int r = tid - 32; r < nch * 32; r += 96) asm volatile("prefetch.global.L2 [%0];" ::"l"(p.ssm_k + (size_t)ch0 * S_ + r * 64));
      const uint32_t sh0 = __byte_perm(sa.x, sb2.x, 0x5410), sh1 = __byte_perm(sa.x, sb2.x, 0x7632);
      const uint32_t sh2 = __byte_perm(sa.y, sb2.y, 0x5410), sh3 = __byte_perm(sa.y, sb2.y, 0x7632);
      mbar_wait(BAR(BAR_KVIN), 0);
      if (tid == 96) DBG_T(19);
#pragma unroll 1
      for (int c = hw; c < 8; c += 3) {
        const uint32_t ka = sb + SM_KVK + 16 * c * 112 + 4 * pp, va = sb + SM_KVV + 16 * c * 112 + 4 * pp;
        uint32_t w0[2][4], w1[2][4];
        uint32_t km3 = lds32(ka), km2 = lds32(ka + 112), km1 = lds32(ka + 224);
#pragma unroll
        for (int hh = 0; hh < 2; hh++) {
          uint32_t kv[8];
#pragma unroll
          for (int t = 0; t < 8; t++) {
            const uint32_t kk = lds32(ka + (8 * hh + t + 3) * 112), vv = lds32(va + (8 * hh + t) * 112);
            uint32_t a = hmul2(km3, sh3);
            a = hadd2(a, hmul2(km2, sh2));
            a = hadd2(a, hmul2(km1, sh1));
            a = hadd2(a, hmul2(kk, sh0));
            kv[t] = hmul2(a, vv);
            km3 = km2; km2 = km1; km1 = kk;
          }
#pragma unroll
          for (int q = 0; q < 2; q++) {
            w0[0][2 * hh + q] = __byte_perm(kv[4 * q + 3], kv[4 * q + 2], 0x5410);
            w1[0][2 * hh + q] = __byte_perm(kv[4 * q + 3], kv[4 * q + 2], 0x7632);
            w0[1][2 * hh + q] = __byte_perm(kv[4 * q + 1], kv[4 * q], 0x5410);
            w1[1][2 * hh + q] = __byte_perm(kv[4 * q + 1], kv[4 * q], 0x7632);
          }
        }
        if (lane < 28) {
#pragma unroll
          for (int half = 0; half < 2; half++) {
            const int r0 = half * 28 + pp, r1 = (2 + half) * 28 + pp;
            sts128(sb + SM_KVO + r0 * 128 + ((c ^ (r0 & 7)) << 4), w0[half][0], w0[half][1], w0[half][2], w0[half][3]);
            sts128(sb + SM_KVO + r1 * 128 + ((c ^ (r1 & 7)) << 4), w1[half][0], w1[half][1], w1[half][2], w1[half][3]);
          }
        }
      }
      fence_async_smem();
      named_bar(7, 96);
      if (tid == 96) DBG_T(20);
      if (hw == 1) {
        mbar_wait(BAR(BAR_P0), 1);
        stage_prefetch(bi + 32);
        uint4* zc = g_z[(epoch + 1) & 1] + (size_t)blockIdx.x * (D_ * 2) + lane;
#pragma unroll 1
        for (int i = 0; i < 28; i++) { zc[32 * i] = make_uint4(0, 0, 0, 0); __nanosleep(20); }
      }
      if (lane == 0) {
        if (hw == 2) {
#pragma unroll 1
          for (int i = 0; i < 4; i++) {
            tma5d_store(&tm_kvt, sb + SM_KVO + i * 28 * 128, 28 * bj, i & 1, i >> 1, bi);
            if (i < 3) __nanosleep(PACE_NS);
          }
          asm volatile("cp.async.bulk.commit_group;\ncp.async.bulk.wait_group 0;\nfence.proxy.async.global;" ::: "memory");
          DBG_T(21);
          signal_counter(&g_cnt_kv[0]);
          DBG_T(22);
        }
        if (hw == 0) {
          mbar_wait(BAR(BAR_STG), 0);
          asm volatile("fence.acq_rel.gpu;" ::: "memory");
#pragma unroll
          for (int w = 0; w < 4; w++) asm volatile("red.relaxed.gpu.global.add.u32 [%0], 1;" ::"l"(&g_cnt_part[(bi * 8 + 4 * rank + w) * 8]) : "memory");
        }
      }
      __syncwarp();
      if (hw == 0) {
        mbar_wait(BAR(BAR_XT), 0);
        const int row = lane & 15, hf = lane >> 4;
        float s1 = 0.f, s2 = 0.f, s1b = 0.f, s2b = 0.f;
        uint32_t first = lds32(sb + SM_XT + row * 128 + ((row & 7) << 4));
        const float x0 = bf_lo(first);
#pragma unroll 1
        for (int q = 0; q < 7; q++) {
#pragma unroll
          for (int c = 0; c < 4; c++) {
            const uint4 v = lds128(sb + SM_XT + q * 2048 + row * 128 + (((4 * hf + c) ^ (row & 7)) << 4));
            const uint32_t ww[4] = {v.x, v.y, v.z, v.w};
#pragma unroll
            for (int i = 0; i < 4; i++) {
              const float lo = bf_lo(ww[i]) - x0, hi = bf_hi(ww[i]) - x0;
              s1 += lo; s2 = fmaf(lo, lo, s2); s1b += hi; s2b = fmaf(hi, hi, s2b);
            }
          }
        }
        s1 += s1b; s2 += s2b;
        s1 += __shfl_xor_sync(0xffffffffu, s1, 16); s2 += __shfl_xor_sync(0xffffffffu, s2, 16);
        const float dm = s1 * (1.f / D_);
        const float var = fmaxf(s2 * (1.f / D_) - dm * dm, 0.f);
        const float mb = bf_round(x0 + dm);
        const float rs = rcp_approx(bf_round(sqrt_approx(bf_round(bf_round(var) + 1e-5f))));
        if (hf == 0) asm volatile("st.shared.v2.b32 [%0], {%1, %2};" ::"r"(sb + SM_STATS + row * 8), "r"(pack_bf16(mb, mb)), "r"(__float_as_uint(rs)) : "memory");
        __syncwarp();
        if (lane == 0) mbar_arrive(BAR(BAR_STAT));
      }
      if (hw == 2) {
        for (int c = 0; c < nch; c++) {
          const uint32_t cb = sb + SM_CH + c * CH_B;
          if (lane < 2) sts128(cb + lane * 16, 0, 0, 0, 0);
          for (int z = lane; z < CH_PAD / 16; z += 32) { sts128(cb + CH_HB + z * 16, 0, 0, 0, 0); sts128(cb + CH_HB + CH_UH + z * 16, 0, 0, 0, 0); }
        }
        fence_async_smem();
        __syncwarp();
        if (lane == 0) {
          wait_counter(&g_cnt_kv[0], (epoch + 1) * NCTA);
          DBG_T(16);
          fence_async_all();
          for (int c = 0; c < nch; c++) {
            const uint32_t cb = sb + SM_CH + c * CH_B, cbar = BAR(BAR_CFULL + c);
            const int d = ch0 + c;
            mbar_expect_tx(cbar, 8192);
            bulk_load(cb + 32, p.ssm_k + (size_t)d * S_, 4096, cbar);
            bulk_load(cb + CH_HB + CH_PAD, (const uint8_t*)g_kvt + (size_t)d * 4096, 2048, cbar);
            bulk_load(cb + CH_HB + CH_PAD + CH_UH, (const uint8_t*)g_kvt + (size_t)d * 4096 + 2048, 2048, cbar);
            __nanosleep(PACE_NS);
          }
        }
        __syncwarp();
      }
    }
    named_bar(3, 128);
    if (tid == 0) g_epoch[blockIdx.x * 8] = epoch + 1;
  } else {
    asm volatile("setmaxnreg.inc.sync.aligned.u32 %0;" ::"n"(REG_C));
    const int cw = warp - 4, g = cw >> 2, w = cw & 3;
    const int t128 = tid & 127;
    const bool elect = t128 == 0;
    const bool keeper = g == rank;
    if (keeper) bar_arrive(4 + (g ^ 1), 256);
    if (tid == 128) DBG_CK(67);
    asm volatile("barrier.cluster.wait.aligned;" ::: "memory");
    if (tid == 128) DBG_CK(68);
    const uint64_t descB0 = mkdesc(sb, 8192, 1024, 1);

    {
      uint32_t xf[28][4];
      float sum[4][4];
#pragma unroll
      for (int i = 0; i < 4; i++) sum[i][0] = sum[i][1] = sum[i][2] = sum[i][3] = 0.f;
      {
        const int xr = 64 * g + 16 * w + (lane & 7) + 8 * ((lane >> 3) & 1);
        const uint32_t xa = sb + SM_XN + xr * 128;
#pragma unroll
        for (int kc = 0; kc < 7; kc++) {
          mbar_wait(BAR(BAR_XF + kc), 0);
          if (elect && g == 0 && (kc == 0 || kc == 6)) DBG_T(kc == 0 ? 17 : 18);
#pragma unroll
          for (int ks = 0; ks < 4; ks++) {
            uint32_t(&f)[4] = xf[4 * kc + ks];
            asm volatile("ldmatrix.sync.aligned.m8n8.x4.shared.b16 {%0,%1,%2,%3}, [%4];" : "=r"(f[0]), "=r"(f[1]), "=r"(f[2]), "=r"(f[3])
                         : "r"(xa + kc * 16384 + (((2 * ks + (lane >> 4)) ^ (xr & 7)) << 4)));
            mma16816(sum[ks], f[0], f[1], f[2], f[3], 0x3F803F80u, 0x3F803F80u);
          }
        }
      }
      __syncwarp();
      if (lane == 0) mbar_arrive(BAR(BAR_XFREE));
      const float mean0 = ((sum[0][0] + sum[1][0]) + (sum[2][0] + sum[3][0])) * (1.f / D_), mean1 = ((sum[0][2] + sum[1][2]) + (sum[2][2] + sum[3][2])) * (1.f / D_);
      const float mb0 = bf_round(mean0), mb1 = bf_round(mean1);
      const uint32_t m20 = pack_bf16(mb0, mb0), m21 = pack_bf16(mb1, mb1);
      if (elect) DBG_T(1 + g);
      auto center = [&](int kc) {
#pragma unroll
        for (int ks = 0; ks < 4; ks++) {
          uint32_t(&f)[4] = xf[4 * kc + ks];
          f[0] = hsub2(f[0], m20); f[1] = hsub2(f[1], m21); f[2] = hsub2(f[2], m20); f[3] = hsub2(f[3], m21);
          fence_r4(f[0], f[1], f[2], f[3]);
        }
      };
      center(0);
      const uint32_t lo0 = p.up_first ? 0xFF80FF80u : 0u, lo1 = p.up_first ? 0u : 0xFF80FF80u;
      uint32_t h[64];
      const uint32_t ha0 = sb + SM_HS + g * 8192 + t128 * 16;
      auto gu_pass = [&](float (&acc)[64], int ps, auto hook) {
        uint32_t dlo = (uint32_t)descB0;
        asm volatile("" : "+r"(dlo));
        const uint64_t descP = (descB0 & 0xFFFFFFFF00000000ull) | dlo;
#pragma unroll
        for (int kc = 0; kc < 7; kc++) {
          mbar_wait(BAR(BAR_FULL + kc), ps & 1);
          if (keeper ? kc <= 4 : (kc == 0 || kc >= 3)) named_bar(4 + g, 256);
          wg_fence();
          const uint64_t db = descP + gu_slot(kc) / 16;
#pragma unroll
          for (int ks = 0; ks < 4; ks++) {
            const uint32_t(&f)[4] = xf[4 * kc + ks];
            if (kc == 0 && ks == 0) wgmma_rs_n128_mn<0>(acc, f[0], f[1], f[2], f[3], db);
            else wgmma_rs_n128_mn<1>(acc, f[0], f[1], f[2], f[3], db + ks * 128);
          }
          wg_commit();
          if (keeper ? (kc <= 3 || kc == 6) : kc >= 2) bar_arrive(4 + (g ^ 1), 256);
          if (kc > 0) { wg_wait<1>(); if (elect) mbar_arrive(BAR(BAR_EMPTY + kc - 1)); }
          hook(kc);
        }
        wg_wait<0>();
        fence_acc(acc);
        if (elect) mbar_arrive(BAR(BAR_EMPTY + 6));
      };
      auto h_word = [&](const float (&acc)[64], int o) {
        return hmul2(hmax2(pack_bf16(acc[o], acc[o + 1]), lo0), hmax2(pack_bf16(acc[32 + o], acc[33 + o]), lo1));
      };
#pragma unroll 1
      for (int ps = 0; ps < natom - 1; ps++) {
        float acc[64];
        gu_pass(acc, ps, [&](int kc) { if (ps == 0 && kc < 6) center(kc + 1); });
        if (ps == 0) mbar_wait(BAR(BAR_XFREE), 0);
#pragma unroll
        for (int u = 0; u < 4; u++)
          sts128(ha0 + ps * 16384 + u * 2048, h_word(acc, 8 * u), h_word(acc, 8 * u + 2), h_word(acc, 8 * u + 4), h_word(acc, 8 * u + 6));
        if (elect && ps < 2) mbar_arrive(BAR(BAR_P0));
        if (elect && ps == 0) DBG_T(3 + g);
      }
      {
        float acc[64];
        gu_pass(acc, natom - 1, [&](int kc) {
          if (kc >= 1 && kc <= 3) {
            if (kc < 3 || typeA) {
#pragma unroll
              for (int u = 0; u < 4; u++) {
                const uint4 v = lds128(ha0 + (kc - 1) * 16384 + u * 2048);
                const int o = 16 * (kc - 1) + 4 * u;
                h[o] = v.x; h[o + 1] = v.y; h[o + 2] = v.z; h[o + 3] = v.w;
              }
            } else {
#pragma unroll
              for (int i = 32; i < 48; i++) h[i] = 0;
            }
          }
          if (kc == 4) {
            __syncwarp();
            if (lane == 0) { mbar_arrive(BAR(BAR_HFREE)); mbar_arrive_cluster(mapa(BAR(BAR_PEER), rank ^ 1)); }
          }
        });
#pragma unroll
        for (int i = 0; i < 16; i++) h[48 + i] = h_word(acc, 2 * i);
        if (elect && natom == 2) mbar_arrive(BAR(BAR_P0));
      }
      if (elect) DBG_T(5 + g);
#pragma unroll
      for (int i = 0; i < 64; i += 4) fence_r4(h[i], h[i + 1], h[i + 2], h[i + 3]);
      P2 p2;
      p2.sb = sb; p2.bars = bars; p2.g = g; p2.elect = elect;
      const int ft = fresh_tid(), fc = fresh_cta(), fl = ft & 31, fw = (ft >> 5) - 4;
      const uint32_t peer_recv = mapa(sb + SM_RECV + (fw & 3) * 2048 + fl * 16, (fc & 1) ^ 1), peer_bars = mapa(bars, (fc & 1) ^ 1);
      uint4* pout = g_part + ((size_t)((fc >> 3) * 8 + fw) * 4 + ((fc & 7) >> 1)) * (28 * 32) + fl;
      if (typeA) phase2<8>(h, p2, keeper, peer_recv, peer_bars, pout, ft & 127, fl);
      else phase2<4>(h, p2, keeper, peer_recv, peer_bars, pout, ft & 127, fl);
    }
    if (elect) DBG_T(7 + g);
    {
    const int tid = fresh_tid(), cta = fresh_cta();
    const int lane = tid & 31, cw = __shfl_sync(0xffffffffu, (tid >> 5) - 4, 0), w = cw & 3;
    const int bi = cta >> 3, bj = cta & 7;
    const bool typeA = (bj & 2) == 0;
    const int nch = typeA ? NCH_A : NCH_B;
    const int ch0 = (bi * 2 + (bj >> 2)) * (2 * NCH_A + 2 * NCH_B) + (typeA ? (bj & 1) * NCH_A : 2 * NCH_A + (bj & 1) * NCH_B);
    const uint32_t zpar = lds32(sb + SM_BARS + 480) & 1;
    {
      const int r0 = lane >> 2, c = lane & 3;
      const uint32_t rbase = sb + SM_RED + g * RED_B;
      const int ord = (g == (bj & 1)) ? 1 : 0;
      const bool turns = CONV_TURNS && nch > 2;
      if (turns && ord == 1) bar_arrive(8 + (g ^ 1), 256);
#pragma unroll 1
      for (int ci = ord; ci < nch; ci += 2) {
        const int d = ch0 + ci;
        const uint32_t cb = sb + SM_CH + ci * CH_B;
        const uint32_t D2 = __byte_perm((uint32_t)__ldg((const unsigned short*)p.ssm_D + d), 0, 0x1010);
        mbar_wait(BAR(BAR_CFULL + ci), 0);
        const uint32_t hw = cb + 32 + (128 * w + 2 * r0 - 4 * c - 2) * 2;
        const uint64_t db0 = mkdesc(cb + CH_HB + CH_PAD, CH_UH, 128, 0);
        float acc[4][16];
        float aLo[32], aHi[32], aG1[16], aG3[16];
        uint32_t A[4][4][4];
        auto loadRaw = [&](int buf, int j) {
#pragma unroll
          for (int m = 0; m < 4; m++) {
            const uint32_t ad = hw + j * 32 + m * 1024;
            A[buf][m][1] = lds32(ad - 4); A[buf][m][0] = lds32(ad); A[buf][m][2] = lds32(ad + 4);
          }
        };
        loadRaw(0, 0); loadRaw(1, 1);
        if (turns) named_bar(8 + g, 256);
#pragma unroll
        for (int j = 0; j < 8; j++) {
          const int buf = j & 3;
#pragma unroll
          for (int m = 0; m < 4; m++) {
            A[buf][m][3] = __byte_perm(A[buf][m][0], A[buf][m][2], 0x5432);
            A[buf][m][1] = __byte_perm(A[buf][m][1], A[buf][m][0], 0x5432);
            fence_r4(A[buf][m][0], A[buf][m][1], A[buf][m][2], A[buf][m][3]);
          }
          wg_fence();
          {
            const uint64_t dj = db0 - j;
            if (j == 0) {
              wgmma_rs_n64_k<0>(aLo, A[buf][0][0], A[buf][0][1], A[buf][0][2], A[buf][0][3], dj);
              wgmma_rs_n64_k<0>(aHi, A[buf][0][0], A[buf][0][1], A[buf][0][2], A[buf][0][3], dj + 64);
              wgmma_rs_n32_k<0>(aG1, A[buf][1][0], A[buf][1][1], A[buf][1][2], A[buf][1][3], dj);
              wgmma_rs_n32_k<0>(aG3, A[buf][3][0], A[buf][3][1], A[buf][3][2], A[buf][3][3], dj);
            } else {
              wgmma_rs_n64_k<1>(aLo, A[buf][0][0], A[buf][0][1], A[buf][0][2], A[buf][0][3], dj);
              wgmma_rs_n64_k<1>(aHi, A[buf][0][0], A[buf][0][1], A[buf][0][2], A[buf][0][3], dj + 64);
              wgmma_rs_n32_k<1>(aG1, A[buf][1][0], A[buf][1][1], A[buf][1][2], A[buf][1][3], dj);
              wgmma_rs_n32_k<1>(aG3, A[buf][3][0], A[buf][3][1], A[buf][3][2], A[buf][3][3], dj);
            }
            wgmma_rs_n64_k<1>(aHi, A[buf][1][0], A[buf][1][1], A[buf][1][2], A[buf][1][3], dj + 32);
            wgmma_rs_n64_k<1>(aHi, A[buf][2][0], A[buf][2][1], A[buf][2][2], A[buf][2][3], dj);
          }
          wg_commit();
          if (j < 6) {
            if (j >= 2) wg_wait<2>();
            loadRaw((j + 2) & 3, j + 2);
          }
        }
        if (turns && ci + 1 < nch) bar_arrive(8 + (g ^ 1), 256);
        wg_wait<0>();
        fence_acc(aLo); fence_acc(aHi); fence_acc(aG1); fence_acc(aG3);
#pragma unroll
        for (int i = 0; i < 16; i++) { acc[0][i] = aLo[i]; acc[1][i] = aLo[16 + i] + aG1[i]; acc[2][i] = aHi[i]; acc[3][i] = aHi[16 + i] + aG3[i]; }
        if (ci == ord) mbar_wait(BAR(BAR_STG), 0);
        named_bar(1 + g, 128);
        {
          const uint32_t rw = rbase + w * (12 * 512) + lane * 16;
#pragma unroll
          for (int gg = 0; gg < 4; gg++)
#pragma unroll
            for (int b = 1; b < 4; b++) sts128f(rw + (3 * gg + b - 1) * 512, acc[gg][4 * b], acc[gg][4 * b + 1], acc[gg][4 * b + 2], acc[gg][4 * b + 3]);
        }
        named_bar(1 + g, 128);
        float s[4][4];
#pragma unroll
        for (int i = 0; i < 4; i++) { s[i][0] = acc[i][0]; s[i][1] = acc[i][1]; s[i][2] = acc[i][2]; s[i][3] = acc[i][3]; }
#pragma unroll
        for (int dw = 1; dw < 4; dw++) {
          const int w2 = (w - dw) & 3;
          const bool wrap = w < dw;
          const uint32_t ra = rbase + w2 * (12 * 512) + (dw - 1 - (wrap ? 3 : 0)) * 512 + lane * 16;
#pragma unroll
          for (int i = 0; i < 4; i++) {
            if (i > 0 || !wrap) {
              const uint4 v = lds128(ra + i * 3 * 512);
              s[i][0] += __uint_as_float(v.x); s[i][1] += __uint_as_float(v.y); s[i][2] += __uint_as_float(v.z); s[i][3] += __uint_as_float(v.w);
            }
          }
        }
        const uint32_t ua = cb + CH_HB + CH_PAD + ((r0 & 1) ? 0 : CH_UH) + (8 * w + 2 * c) * 16 + (r0 >> 1) * 4;
        uint32_t* zp = (uint32_t*)g_z[zpar] + ((size_t)(8 * w + 2 * c) * D_ + d) * 8 + (r0 ^ (d & 4));
#pragma unroll
        for (int i = 0; i < 4; i++) {
#pragma unroll
          for (int e = 0; e < 2; e++) {
            uint32_t kvw = lds32(ua + (32 * i + e) * 16);
            kvw = __byte_perm(kvw, kvw, 0x1032);
            zp[(size_t)(32 * i + e) * D_ * 8] = ~hadd2(pack_bf16(s[i][2 + e], s[i][e]), hmul2(kvw, D2));
          }
        }
        named_bar(1 + g, 128);
        if ((tid & 127) == 0) asm volatile("red.relaxed.gpu.global.add.u32 [%0], 1;" ::"l"(&g_cnt_z[0]) : "memory");
      }
    }
    if (elect) DBG_T(12 + g);
    if (cw < 7) {
      const int r0 = lane >> 2;
      mbar_wait(BAR(BAR_XT), 0);
      mbar_wait(BAR(BAR_STAT), 0);
      uint32_t m2[2], rh2[2], rl2[2];
      float rsq[2];
#pragma unroll
      for (int e = 0; e < 2; e++) {
        uint32_t a, b;
        asm volatile("ld.shared.v2.b32 {%0, %1}, [%2];" : "=r"(a), "=r"(b) : "r"(sb + SM_STATS + (r0 + 8 * e) * 8));
        const float rs = __uint_as_float(b), rh = bf_round(rs);
        m2[e] = a; rh2[e] = pack_bf16(rh, rh); rl2[e] = pack_bf16(rs - rh, rs - rh); rsq[e] = rs * rs;
      }
      const int xr = (lane & 7) + 8 * ((lane >> 3) & 1);
      const uint32_t xbox = sb + SM_XT + cw * 2048 + xr * 128;
      uint32_t xf[4][4], bsum[4][4], xn[4][4];
#pragma unroll
      for (int u = 0; u < 4; u++) {
        const uint32_t xa = xbox + (((2 * u + (lane >> 4)) ^ (xr & 7)) << 4);
        asm volatile("ldmatrix.sync.aligned.m8n8.x4.shared.b16 {%0,%1,%2,%3}, [%4];" : "=r"(xf[u][0]), "=r"(xf[u][1]), "=r"(xf[u][2]), "=r"(xf[u][3]) : "r"(xa));
#pragma unroll
        for (int i = 0; i < 4; i++) xn[u][i] = ln_apply(xf[u][i], m2[i & 1], rh2[i & 1], rl2[i & 1]);
      }
      mbar_wait(BAR(BAR_PT), 0);
#pragma unroll
      for (int u = 0; u < 4; u++) {
        float a[8];
#pragma unroll
        for (int s = 0; s < 4; s++) {
          const uint4 v = lds128(sb + SM_PT + s * 14336 + ((4 * cw + u) * 32 + lane) * 16);
          if (s == 0) { a[0] = bf_lo(v.x); a[1] = bf_hi(v.x); a[2] = bf_lo(v.y); a[3] = bf_hi(v.y); a[4] = bf_lo(v.z); a[5] = bf_hi(v.z); a[6] = bf_lo(v.w); a[7] = bf_hi(v.w); }
          else { a[0] += bf_lo(v.x); a[1] += bf_hi(v.x); a[2] += bf_lo(v.y); a[3] += bf_hi(v.y); a[4] += bf_lo(v.z); a[5] += bf_hi(v.z); a[6] += bf_lo(v.w); a[7] += bf_hi(v.w); }
        }
        bsum[u][0] = pack_bf16(a[0] * rsq[0], a[1] * rsq[0]); bsum[u][1] = pack_bf16(a[2] * rsq[1], a[3] * rsq[1]);
        bsum[u][2] = pack_bf16(a[4] * rsq[0], a[5] * rsq[0]); bsum[u][3] = pack_bf16(a[6] * rsq[1], a[7] * rsq[1]);
      }
      mbar_wait(BAR(BAR_ZT), 0);
      {
        const uint4* zg = g_z[zpar] + ((size_t)(bi * 8 + bj) * D_ + 64 * cw) * 2 + lane;
        uint4 zv[4];
        uint32_t pending = 0xF;
#pragma unroll 1
        for (uint32_t it = 0; it < (1u << 16); it++) {
#pragma unroll
          for (int i = 0; i < 4; i++)
            if (pending >> i & 1)
              asm volatile("ld.relaxed.gpu.global.v4.b32 {%0,%1,%2,%3}, [%4];" : "=r"(zv[i].x), "=r"(zv[i].y), "=r"(zv[i].z), "=r"(zv[i].w) : "l"(zg + 32 * i) : "memory");
#pragma unroll
          for (int i = 0; i < 4; i++)
            if (zv[i].x != 0 && zv[i].y != 0 && zv[i].z != 0 && zv[i].w != 0) pending &= ~(1u << i);
          if (__all_sync(0xffffffffu, pending == 0)) break;
        }
#pragma unroll
        for (int i = 0; i < 4; i++) {
          sts128(sb + SM_ZT + cw * 2048 + (32 * i + lane) * 16, ~zv[i].x, ~zv[i].y, ~zv[i].z, ~zv[i].w);
        }
        __syncwarp();
      }
#pragma unroll
      for (int u = 0; u < 4; u++) {
        const int mi = lane >> 3;
        const int dz = 64 * cw + 16 * u + 8 * (mi >> 1) + (lane & 7);
        const uint32_t za = sb + SM_ZT + dz * 32 + (((mi & 1) ^ ((dz >> 2) & 1)) << 4);
        uint32_t z[4];
        asm volatile("ldmatrix.sync.aligned.m8n8.x4.trans.shared.b16 {%0,%1,%2,%3}, [%4];" : "=r"(z[0]), "=r"(z[1]), "=r"(z[2]), "=r"(z[3]) : "r"(za));
        uint32_t o[4];
#pragma unroll
        for (int i = 0; i < 4; i++) o[i] = hadd2(hadd2(xf[u][i], hmul2(xn[u][i], z[i])), bsum[u][i]);
        const uint32_t xa = xbox + (((2 * u + (lane >> 4)) ^ (xr & 7)) << 4);
        asm volatile("stmatrix.sync.aligned.m8n8.x4.shared.b16 [%0], {%1,%2,%3,%4};" ::"r"(xa), "r"(o[0]), "r"(o[1]), "r"(o[2]), "r"(o[3]) : "memory");
      }
      __syncwarp();
#pragma unroll
      for (int i = 0; i < 4; i++) {
        const int row = 4 * i + (lane >> 3), ch = lane & 7;
        const uint4 v = lds128(sb + SM_XT + cw * 2048 + row * 128 + ((ch ^ (row & 7)) << 4));
        *(uint4*)(p.out + (size_t)(bi * 128 + bj * 16 + row) * D_ + cw * 64 + ch * 8) = v;
      }
    }
    }
    if (elect) DBG_T(14 + g);
  }
}

typedef CUresult (*EncodeFn)(CUtensorMap*, CUtensorMapDataType, cuuint32_t, void*, const cuuint64_t*, const cuuint64_t*, const cuuint32_t*,
                             const cuuint32_t*, CUtensorMapInterleave, CUtensorMapSwizzle, CUtensorMapL2promotion, CUtensorMapFloatOOBfill);

bool make_map(EncodeFn enc, CUtensorMap* m, const void* ptr, uint64_t inner, uint64_t outer, uint32_t box_inner, uint32_t box_outer,
              CUtensorMapSwizzle sw = CU_TENSOR_MAP_SWIZZLE_128B) {
  cuuint64_t dims[2] = {inner, outer};
  cuuint64_t strides[1] = {inner * 2};
  cuuint32_t box[2] = {box_inner, box_outer};
  cuuint32_t es[2] = {1, 1};
  return enc(m, CU_TENSOR_MAP_DATA_TYPE_BFLOAT16, 2, const_cast<void*>(ptr), dims, strides, box, es, CU_TENSOR_MAP_INTERLEAVE_NONE,
             sw, CU_TENSOR_MAP_L2_PROMOTION_L2_256B, CU_TENSOR_MAP_FLOAT_OOB_FILL_NONE) == CUDA_SUCCESS;
}

}

extern "C" void kernel_launch(void* const* d_in, const int* in_sizes, int n_in, void* d_out, int out_size) {
  (void)in_sizes; (void)n_in; (void)out_size;
  static EncodeFn enc = nullptr;
  if (!enc) {
    void* fn = nullptr;
    cudaDriverEntryPointQueryResult st;
    cudaGetDriverEntryPoint("cuTensorMapEncodeTiled", &fn, cudaEnableDefault, &st);
    enc = (EncodeFn)fn;
    cudaFuncSetAttribute(fused_kernel, cudaFuncAttributeMaxDynamicSharedMemorySize, SMEM_BYTES);
  }
  CUtensorMap tm_wgu, tm_wd128, tm_wd64, tm_x128, tm_x16, tm_k, tm_v, tm_kvt;
  const uintptr_t pg = (uintptr_t)d_in[7], pu = (uintptr_t)d_in[8];
  {
    cuuint64_t dims[3] = {F_, D_, 2};
    cuuint64_t strides[2] = {F_ * 2, pg < pu ? pu - pg : pg - pu};
    cuuint32_t box[3] = {64, 64, 2};
    cuuint32_t es[3] = {1, 1, 1};
    enc(&tm_wgu, CU_TENSOR_MAP_DATA_TYPE_BFLOAT16, 3, (void*)(pg < pu ? pg : pu), dims, strides, box, es, CU_TENSOR_MAP_INTERLEAVE_NONE,
        CU_TENSOR_MAP_SWIZZLE_128B, CU_TENSOR_MAP_L2_PROMOTION_L2_256B, CU_TENSOR_MAP_FLOAT_OOB_FILL_NONE);
  }
  make_map(enc, &tm_x128, d_in[0], D_, S_, 64, 128);
  make_map(enc, &tm_wd128, d_in[9], D_, F_, 64, 128);
  make_map(enc, &tm_wd64, d_in[9], D_, F_, 64, 64);
  make_map(enc, &tm_x16, d_in[0], D_, S_, 64, 16);
  Params p;
  make_map(enc, &tm_k, d_in[1], D_, S_, 56, 32, CU_TENSOR_MAP_SWIZZLE_NONE);
  make_map(enc, &tm_v, d_in[2], D_, S_, 56, 32, CU_TENSOR_MAP_SWIZZLE_NONE);
  {
    static void* kvt = nullptr;
    if (!kvt) cudaGetSymbolAddress(&kvt, g_kvt);
    cuuint64_t dims[5] = {64, 224, 2, 2, 16};
    cuuint64_t strides[4] = {8192, 2048, 4096, 128};
    cuuint32_t box[5] = {64, 28, 1, 1, 1};
    cuuint32_t es[5] = {1, 1, 1, 1, 1};
    enc(&tm_kvt, CU_TENSOR_MAP_DATA_TYPE_BFLOAT16, 5, kvt, dims, strides, box, es, CU_TENSOR_MAP_INTERLEAVE_NONE, CU_TENSOR_MAP_SWIZZLE_128B,
        CU_TENSOR_MAP_L2_PROMOTION_NONE, CU_TENSOR_MAP_FLOAT_OOB_FILL_NONE);
  }
  p.out = (__nv_bfloat16*)d_out;
  p.up_first = pu < pg;
  p.wg = (const __nv_bfloat16*)d_in[7];
  p.wu = (const __nv_bfloat16*)d_in[8];
  p.wd = (const __nv_bfloat16*)d_in[9];
  p.x = (const __nv_bfloat16*)d_in[0];
  p.k = (const __nv_bfloat16*)d_in[1];
  p.v = (const __nv_bfloat16*)d_in[2];
  p.shift_k = (const __nv_bfloat16*)d_in[3];
  p.ssm_k = (const __nv_bfloat16*)d_in[4];
  p.ssm_D = (const __nv_bfloat16*)d_in[5];
  fused_kernel<<<NCTA, NTHREADS, SMEM_BYTES, cudaStreamPerThread>>>(tm_wgu, tm_wd128, tm_wd64, tm_x128, tm_x16, tm_k, tm_v, tm_kvt, p);
}
```
